```python
import torch

def _softmax(x, axis=-1):
    return torch.softmax(x, dim=axis)
def _gelu(x):
    return torch.nn.functional.gelu(x, approximate="tanh")
def _silu(x):
    return torch.nn.functional.silu(x)
def _sigmoid(x):
    return torch.sigmoid(x)
def _layernorm(x, axis=-1, eps=1e-5):
    m = x.mean(dim=axis, keepdim=True)
    v = x.var(dim=axis, keepdim=True, unbiased=False)
    return (x - m) / torch.sqrt(v + eps)
def _scatter_add(tgt, idx, src, axis=0):
    return tgt.clone().index_add_(axis, idx, src)
def _segment_sum(src, seg, n):
    out = torch.zeros((n,) + src.shape[1:], dtype=src.dtype)
    return out.index_add_(0, seg, src)
def _pad(x, pw):
    flat = tuple(v for pair in reversed(pw) for v in pair)
    return torch.nn.functional.pad(x, flat)

kernel_name = 'sequential_preLN__compressed_kv_cla__dense_activation_silu__decode'

def setup_inputs():

    _w = (lambda a: (lambda t: t.to(torch.bfloat16) if t.is_floating_point() else t)(torch.as_tensor(a)))
    def _A_setup():
        B, H, Sq, Sk, D, M = 1, 32, 1, 8192, 128, 576
        Dc = 4 * D
        return {
            "x": _w((lambda *s: torch.randn(*s, dtype=torch.bfloat16) * 0.05)(B, Sq, M)),
            "c_kv": _w((lambda *s: torch.randn(*s, dtype=torch.bfloat16) * 0.8)(B, Sk, Dc)),
            "w_q": _w((lambda *s: torch.randn(*s, dtype=torch.bfloat16) * 3.2)(M, H, D) * (M ** -0.5)),
            "w_uk": _w((lambda *s: torch.randn(*s, dtype=torch.bfloat16) * 3.2)(Dc, H, D) * (Dc ** -0.5)),
            "w_uv": _w((lambda *s: torch.randn(*s, dtype=torch.bfloat16) * 0.8)(Dc, H, D) * (Dc ** -0.5)),
            "w_o": _w((lambda *s: torch.randn(*s, dtype=torch.bfloat16) * 0.8)(H, D, M) * ((H * D) ** -0.5)),
        }
    _A_in = _A_setup()

    def _B_setup():
        B, S, D, F = 1, 1, 576, 4608
        return {
            "x": _w((lambda *s: torch.randn(*s, dtype=torch.bfloat16) * 0.05)(B, S, D)),
            "w1": _w((lambda *s: torch.randn(*s, dtype=torch.bfloat16) * 3.2)(D, F) * (D ** -0.5)),
            "w2": _w((lambda *s: torch.randn(*s, dtype=torch.bfloat16) * 0.2)(F, D) * (F ** -0.5)),
        }
    _B_in = _B_setup()

    return {
        "A_x": _A_in["x"],
        "A_c_kv": _A_in["c_kv"],
        "A_w_q": _A_in["w_q"],
        "A_w_uk": _A_in["w_uk"],
        "A_w_uv": _A_in["w_uv"],
        "A_w_o": _A_in["w_o"],
        "B_x": _B_in["x"],
        "B_w1": _B_in["w1"],
        "B_w2": _B_in["w2"],
    }

def reference(A_x, A_c_kv, A_w_q, A_w_uk, A_w_uv, A_w_o, B_x, B_w1, B_w2):
    def _A_ref(x, c_kv, w_q, w_uk, w_uv, w_o):
        B, Sq, M = x.shape[0], x.shape[1], x.shape[2]
        Sk = c_kv.shape[1]
        H, D = w_q.shape[1], w_q.shape[2]
        q = torch.einsum("bqm,mhd->bhqd", x, w_q)
        k = torch.einsum("bkc,chd->bhkd", c_kv, w_uk)
        v = torch.einsum("bkc,chd->bhkd", c_kv, w_uv)
        scores = torch.einsum("bhqd,bhkd->bhqk", q, k) * (D ** -0.5)
        off = Sk - Sq
        qi = torch.arange(Sq)[:, None]
        kj = torch.arange(Sk)[None, :]
        cmask = kj <= (qi + off)
        scores = torch.where(cmask[None, None], scores, -1e9)
        p = _softmax(scores, axis=-1)
        ctx = torch.einsum("bhqk,bhkd->bhqd", p, v)
        return torch.einsum("bhqd,hdm->bqm", ctx, w_o)

    def _B_ref(x, w1, w2):
        h = torch.einsum("bsd,df->bsf", x, w1)
        h = _silu(h)
        out = torch.einsum("bsf,fd->bsd", h, w2)
        return out

    x = A_x
    h = x + _A_ref(_layernorm(x, axis=-1), A_c_kv, A_w_q, A_w_uk, A_w_uv, A_w_o)
    h2 = h + _B_ref(_layernorm(h, axis=-1), B_w1, B_w2)
    return h2
```

```cpp
#include <cuda_runtime.h>
#include <cuda_bf16.h>
#include <cuda.h>
#include <stdint.h>

namespace {

constexpr int NCTA = 128;
constexpr int NFFN = 96;
constexpr int NTHREADS = 384;
constexpr int SPIN_LIMIT = 1 << 22;

constexpr uint32_t R_A = 0;
constexpr uint32_t R_A_WUK = 36864;
constexpr uint32_t R_C = 71680;
constexpr uint32_t R_V = R_C + 65536;
constexpr uint32_t R_O = R_V + 32768;
constexpr uint32_t R_P = R_O + 40960;
constexpr uint32_t R_RED = R_P + 4096;
constexpr uint32_t R_VXN = R_RED + 4096;
constexpr uint32_t VXN_LO = 576 + 16;
constexpr uint32_t R_XQP = R_VXN + 1280;
constexpr uint32_t R_VQ = R_XQP + 1024;
constexpr uint32_t VQ_LO = 256 + 16;
constexpr uint32_t R_VO = R_VQ + 640;
constexpr uint32_t VO_LO = 512 + 16;
constexpr uint32_t R_VC = R_VO + 1088;
constexpr uint32_t VC_LO = 128 + 16;
constexpr uint32_t R_VH = R_VC + 320;
constexpr uint32_t VH_LO = 1152 + 16;
constexpr uint32_t R_VU = R_VH + 2432;
constexpr uint32_t VU_LO = 96 + 16;
constexpr uint32_t R_ZERO = R_VU + 256 + 64;
constexpr uint32_t R_WTS = R_VU + 384;
constexpr uint32_t R_SMAX = R_WTS + 1024;
constexpr uint32_t R_SSUM = R_SMAX + 512;
constexpr uint32_t R_ST = R_SSUM + 512;
constexpr uint32_t R_TAG = R_ST + 512;
constexpr uint32_t R_BAR = R_TAG + 64;
constexpr uint32_t R_TS = R_BAR + 24 * 8;
constexpr uint32_t SMEM_USED = R_TS + 64 * 8;
constexpr uint32_t SMEM_BYTES = SMEM_USED + 1024;
static_assert(SMEM_BYTES <= 232448, "smem");
static_assert(R_P % 1024 == 0 && R_C % 1024 == 0 && R_V % 1024 == 0 && R_O % 1024 == 0, "align");

enum { B_WQ = 0, B_WUK, B_CKV0, B_CKV1, B_CKV2, B_CKV3, B_WUV, B_WO, B_W1, B_W2, B_FS, B_FREEC, B_XQ, B_QA, B_E4, B_FREEA, B_ST, B_IN, B_XC, B_SL, B_HL, B_RST, NBAR };
constexpr uint32_t R_INBOX = R_A + 55296;
constexpr uint32_t R_STST = R_XQP;
static_assert(R_XQP % 128 == 0 && R_INBOX % 128 == 0, "align");
enum { NB_VEC = 1, NB_CMP = 2, NB_WG0 = 3, NB_G1 = 4, NB_G2 = 5, NB_G3 = 6, NB_INIT = 7 };

#define RATE_GBS 2900
#define CKV_CONTIG 1
#define DELAY_E2 600
#define DELAY_E4 300
#define POLL_SLEEP 0
#define L2PROMO 3
#define JIT_GBS 4500
#define RATE2_GBS RATE_GBS
#define POLICY 0
#define EARLY_FLAG 1
#define JIT_AFTER_E4 1
#define PROBE 0
#define BUSY_FROM B_FS
#define LAG_NS 1200
#define JIT2_GBS 3500
#define JIT2_GATE 0
#define PF_AHEAD 0
#define LAG0_NS 700
#define E4_LL 0
#define START_OFF 0
__host__ __device__ constexpr uint32_t pace16(uint32_t bytes, uint32_t nctas = 128) { return (uint32_t)((uint64_t)bytes * nctas * 16u / RATE_GBS); }
__host__ __device__ constexpr uint32_t pace2_16(uint32_t bytes, uint32_t nctas = 128) { return (uint32_t)((uint64_t)bytes * nctas * 16u / RATE2_GBS); }
__host__ __device__ constexpr uint32_t jit16(uint32_t bytes, uint32_t nctas) { return (uint32_t)((uint64_t)bytes * nctas * 16u / JIT_GBS); }
constexpr uint32_t CKV_GS = CKV_CONTIG ? 8192 : 1024;
constexpr uint32_t CKV_BS = CKV_CONTIG ? 1024 : 8192;

constexpr int HREP = 4;

__device__ unsigned g_epoch;
constexpr int FREP = 4;
__device__ __align__(128) uint4 g_flagB[FREP * 128 * 2];
__device__ __align__(128) uint4 g_xq[128 * 8];
__device__ __align__(1024) uint4 g_qabs[2048];
__device__ __align__(1024) uint4 g_opart[64 * 64 * 32];
__device__ __align__(1024) uint4 g_stats[8 * 64 * 2];
__device__ __align__(128) uint4 g_pE6[18 * 64 * 8];
__device__ __align__(128) uint4 g_hbuf[HREP * 144];
__device__ __align__(128) uint4 g_pE8[18 * 128 * 8];

#define TS(k) do { } while (0)

struct Params {
    const __nv_bfloat16* x;
    const __nv_bfloat16* wq;
    const char* wuk;
    const char* wo;
    const char* w1;
    const char* w2;
    __nv_bfloat16* out;
};

__device__ __forceinline__ uint32_t smem_u32(const void* p) { return (uint32_t)__cvta_generic_to_shared(p); }
__device__ __forceinline__ void mbar_init(uint32_t bar, uint32_t cnt) {
    asm volatile("mbarrier.init.shared::cta.b64 [%0], %1;" ::"r"(bar), "r"(cnt) : "memory");
}
__device__ __forceinline__ void mbar_expect_tx(uint32_t bar, uint32_t bytes) {
    asm volatile("mbarrier.arrive.expect_tx.shared::cta.b64 _, [%0], %1;" ::"r"(bar), "r"(bytes) : "memory");
}
__device__ __forceinline__ void mbar_arrive(uint32_t bar) {
    asm volatile("mbarrier.arrive.shared::cta.b64 _, [%0];" ::"r"(bar) : "memory");
}
__device__ __forceinline__ bool mbar_try(uint32_t bar, uint32_t parity) {
    uint32_t ok;
    asm volatile("{\n.reg .pred p;\nmbarrier.try_wait.parity.shared::cta.b64 p, [%1], %2;\nselp.u32 %0, 1, 0, p;\n}"
                 : "=r"(ok) : "r"(bar), "r"(parity) : "memory");
    return ok;
}
__device__ __forceinline__ bool mbar_test(uint32_t bar) {
    uint32_t ok;
    asm volatile("{\n.reg .pred p;\nmbarrier.test_wait.parity.shared::cta.b64 p, [%1], 0;\nselp.u32 %0, 1, 0, p;\n}" : "=r"(ok) : "r"(bar) : "memory");
    return ok;
}
__device__ __forceinline__ void mbar_wait(uint32_t bar) {
    int it = 0;
    while (!mbar_try(bar, 0)) { if (++it > SPIN_LIMIT) __trap(); }
}
__device__ __forceinline__ void mbar_wait_cluster(uint32_t bar) {
    int it = 0;
    while (true) {
        uint32_t ok;
        asm volatile("{\n.reg .pred p;\nmbarrier.try_wait.parity.acquire.cluster.shared::cta.b64 p, [%1], 0;\nselp.u32 %0, 1, 0, p;\n}" : "=r"(ok) : "r"(bar) : "memory");
        if (ok) break;
        if (++it > SPIN_LIMIT) __trap();
    }
}
__device__ __forceinline__ uint32_t mapa(uint32_t a, uint32_t rank) { uint32_t d; asm volatile("mapa.shared::cluster.u32 %0, %1, %2;" : "=r"(d) : "r"(a), "r"(rank)); return d; }
__device__ __forceinline__ void st_async_f32(uint32_t a, float v, uint32_t bar) {
    asm volatile("st.async.weak.shared::cluster.mbarrier::complete_tx::bytes.f32 [%0], %1, [%2];" ::"r"(a), "f"(v), "r"(bar) : "memory");
}
__device__ __forceinline__ void st_async_v4(uint32_t a, uint32_t x, uint32_t y, uint32_t z, uint32_t w, uint32_t bar) {
    asm volatile("st.async.weak.shared::cluster.mbarrier::complete_tx::bytes.v4.b32 [%0], {%1,%2,%3,%4}, [%5];" ::"r"(a), "r"(x), "r"(y), "r"(z), "r"(w), "r"(bar) : "memory");
}
__device__ __forceinline__ void nbar_sync(int id, int n) { asm volatile("bar.sync %0, %1;" ::"r"(id), "r"(n) : "memory"); }
__device__ __forceinline__ void nbar_arrive(int id, int n) { asm volatile("bar.arrive %0, %1;" ::"r"(id), "r"(n) : "memory"); }
__device__ __forceinline__ void fence_async_smem() { asm volatile("fence.proxy.async.shared::cta;" ::: "memory"); }

__device__ __forceinline__ void cp_async16(uint32_t dst, const void* src) {
    asm volatile("cp.async.cg.shared.global [%0], [%1], 16;" ::"r"(dst), "l"(src) : "memory");
}
__device__ __forceinline__ void cp_async_arrive(uint32_t bar) {
    asm volatile("cp.async.mbarrier.arrive.noinc.shared::cta.b64 [%0];" ::"r"(bar) : "memory");
}
__device__ __forceinline__ void tma3(uint32_t dst, const CUtensorMap* tm, int c0, int c1, int c2, uint32_t bar) {
    asm volatile("cp.async.bulk.tensor.3d.shared::cluster.global.tile.mbarrier::complete_tx::bytes [%0], [%1, {%2, %3, %4}], [%5];"
                 ::"r"(dst), "l"(tm), "r"(c0), "r"(c1), "r"(c2), "r"(bar) : "memory");
}
__device__ __forceinline__ void tma2(uint32_t dst, const CUtensorMap* tm, int c0, int c1, uint32_t bar) {
    asm volatile("cp.async.bulk.tensor.2d.shared::cluster.global.tile.mbarrier::complete_tx::bytes [%0], [%1, {%2, %3}], [%4];"
                 ::"r"(dst), "l"(tm), "r"(c0), "r"(c1), "r"(bar) : "memory");
}
__device__ __forceinline__ void l2_prefetch(const void* p, uint32_t bytes) {
    asm volatile("cp.async.bulk.prefetch.L2.global [%0], %1;" ::"l"(p), "r"(bytes) : "memory");
}
__device__ __forceinline__ void prefetch_tmap(const CUtensorMap* tm) {
    asm volatile("prefetch.tensormap [%0];" ::"l"(tm) : "memory");
}
__device__ __forceinline__ void ldsm4(uint32_t a, uint32_t& r0, uint32_t& r1, uint32_t& r2, uint32_t& r3) {
    asm volatile("ldmatrix.sync.aligned.m8n8.x4.shared.b16 {%0,%1,%2,%3}, [%4];" : "=r"(r0), "=r"(r1), "=r"(r2), "=r"(r3) : "r"(a) : "memory");
}
__device__ __forceinline__ void ldsm4t(uint32_t a, uint32_t& r0, uint32_t& r1, uint32_t& r2, uint32_t& r3) {
    asm volatile("ldmatrix.sync.aligned.m8n8.x4.trans.shared.b16 {%0,%1,%2,%3}, [%4];" : "=r"(r0), "=r"(r1), "=r"(r2), "=r"(r3) : "r"(a) : "memory");
}
__device__ __forceinline__ void ldsm2(uint32_t a, uint32_t& r0, uint32_t& r1) {
    asm volatile("ldmatrix.sync.aligned.m8n8.x2.shared.b16 {%0,%1}, [%2];" : "=r"(r0), "=r"(r1) : "r"(a) : "memory");
}
__device__ __forceinline__ void stsm4t(uint32_t a, uint32_t r0, uint32_t r1, uint32_t r2, uint32_t r3) {
    asm volatile("stmatrix.sync.aligned.m8n8.x4.trans.shared.b16 [%0], {%1,%2,%3,%4};" ::"r"(a), "r"(r0), "r"(r1), "r"(r2), "r"(r3) : "memory");
}
__device__ __forceinline__ void mma16816(float* d, uint32_t a0, uint32_t a1, uint32_t a2, uint32_t a3, uint32_t b0, uint32_t b1) {
    asm volatile("mma.sync.aligned.m16n8k16.row.col.f32.bf16.bf16.f32 {%0,%1,%2,%3}, {%4,%5,%6,%7}, {%8,%9}, {%0,%1,%2,%3};"
                 : "+f"(d[0]), "+f"(d[1]), "+f"(d[2]), "+f"(d[3]) : "r"(a0), "r"(a1), "r"(a2), "r"(a3), "r"(b0), "r"(b1));
}
__device__ __forceinline__ uint4 ld_relaxed4(const void* p) {
    uint4 v;
    asm volatile("ld.relaxed.gpu.global.v4.u32 {%0,%1,%2,%3}, [%4];" : "=r"(v.x), "=r"(v.y), "=r"(v.z), "=r"(v.w) : "l"(p) : "memory");
    return v;
}
__device__ __forceinline__ uint2 ld_relaxed2(const void* p) {
    uint2 v;
    asm volatile("ld.relaxed.gpu.global.v2.u32 {%0,%1}, [%2];" : "=r"(v.x), "=r"(v.y) : "l"(p) : "memory");
    return v;
}
__device__ __forceinline__ uint32_t ld_relaxed(const void* p) {
    uint32_t v;
    asm volatile("ld.relaxed.gpu.global.u32 %0, [%1];" : "=r"(v) : "l"(p) : "memory");
    return v;
}
__device__ __forceinline__ void st_relaxed4(void* p, uint32_t a, uint32_t b, uint32_t c, uint32_t d) {
    asm volatile("st.relaxed.gpu.global.v4.u32 [%0], {%1,%2,%3,%4};" ::"l"(p), "r"(a), "r"(b), "r"(c), "r"(d) : "memory");
}
__device__ __forceinline__ void st_relaxed2(void* p, uint32_t a, uint32_t b) {
    asm volatile("st.relaxed.gpu.global.v2.u32 [%0], {%1,%2};" ::"l"(p), "r"(a), "r"(b) : "memory");
}
__device__ __forceinline__ void st_relaxed(void* p, uint32_t a) {
    asm volatile("st.relaxed.gpu.global.u32 [%0], %1;" ::"l"(p), "r"(a) : "memory");
}
__device__ __forceinline__ void red_add(unsigned* p, unsigned v) {
    asm volatile("red.relaxed.gpu.global.add.u32 [%0], %1;" ::"l"(p), "r"(v) : "memory");
}
#define XCHG 1
__device__ __forceinline__ void xchg_word(uint32_t* p, uint32_t v) {
    uint32_t old;
    asm volatile("atom.relaxed.gpu.global.exch.b32 %0, [%1], %2;" : "=r"(old) : "l"(p), "r"(v) : "memory");
}
__device__ __forceinline__ void red_max(unsigned* p, unsigned v) {
    asm volatile("red.relaxed.gpu.global.max.u32 [%0], %1;" ::"l"(p), "r"(v) : "memory");
}
__device__ __forceinline__ void sts32(uint32_t a, uint32_t v) { asm volatile("st.shared.u32 [%0], %1;" ::"r"(a), "r"(v) : "memory"); }
__device__ __forceinline__ void sts16(uint32_t a, uint16_t v) { asm volatile("st.shared.u16 [%0], %1;" ::"r"(a), "h"(v) : "memory"); }
__device__ __forceinline__ void stsf(uint32_t a, float v) { asm volatile("st.shared.f32 [%0], %1;" ::"r"(a), "f"(v) : "memory"); }
__device__ __forceinline__ void sts128(uint32_t a, uint32_t x, uint32_t y, uint32_t z, uint32_t w) {
    asm volatile("st.shared.v4.u32 [%0], {%1,%2,%3,%4};" ::"r"(a), "r"(x), "r"(y), "r"(z), "r"(w) : "memory");
}
__device__ __forceinline__ uint4 lds128(uint32_t a) {
    uint4 v; asm volatile("ld.shared.v4.u32 {%0,%1,%2,%3}, [%4];" : "=r"(v.x), "=r"(v.y), "=r"(v.z), "=r"(v.w) : "r"(a) : "memory"); return v;
}
__device__ __forceinline__ uint32_t add_bf16x2(uint32_t a, uint32_t b) { uint32_t r; asm("add.rn.bf16x2 %0, %1, %2;" : "=r"(r) : "r"(a), "r"(b)); return r; }
__device__ __forceinline__ float ldsf(uint32_t a) { float v; asm volatile("ld.shared.f32 %0, [%1];" : "=f"(v) : "r"(a) : "memory"); return v; }
__device__ __forceinline__ uint32_t lds32(uint32_t a) { uint32_t v; asm volatile("ld.shared.u32 %0, [%1];" : "=r"(v) : "r"(a) : "memory"); return v; }
__device__ __forceinline__ float2 ldsf2(uint32_t a) { float2 v; asm volatile("ld.shared.v2.f32 {%0,%1}, [%2];" : "=f"(v.x), "=f"(v.y) : "r"(a) : "memory"); return v; }
__device__ __forceinline__ unsigned gtime() { unsigned t; asm volatile("mov.u32 %0, %%globaltimer_lo;" : "=r"(t)::"memory"); return t; }
__device__ __forceinline__ float ex2(float x) { float y; asm("ex2.approx.ftz.f32 %0, %1;" : "=f"(y) : "f"(x)); return y; }

__device__ __forceinline__ uint32_t tagf(float v, uint32_t tag) { return (__float_as_uint(v) & ~3u) | 2u | tag; }
__device__ __forceinline__ float untag(uint32_t w) { return __uint_as_float(w & ~3u); }
__device__ __forceinline__ bool tags_ok(const uint4& v, uint32_t tag) {
    const uint32_t t = tag | 2u;
    return (((v.x ^ t) | (v.y ^ t) | (v.z ^ t) | (v.w ^ t)) & 3u) == 0;
}
__device__ __forceinline__ bool tags1_ok(const uint4& v, uint32_t tag) { return (((v.x ^ tag) | (v.y ^ tag) | (v.z ^ tag) | (v.w ^ tag)) & 1u) == 0; }
__device__ __forceinline__ int wait_flags16(const uint4* flags, uint32_t val, int lane) {
    bool ok = lane >= 16;
    const uint32_t* f = (const uint32_t*)(flags + 2 * (lane & 15));
    int it = 0;
    while (true) {
        if (!ok) ok = ld_relaxed(f) == val;
        if (__all_sync(0xffffffffu, ok)) break;
        if (++it > SPIN_LIMIT) __trap();
    }
    return it;
}
__device__ __forceinline__ void poll8(uint4* v, const uint4* p, int stride, uint32_t tag) {
    uint32_t pend = 0xffu;
    int it = 0;
    while (true) {
#pragma unroll
        for (int i = 0; i < 8; i++) if (pend & (1u << i)) v[i] = ld_relaxed4(p + i * stride);
#pragma unroll
        for (int i = 0; i < 8; i++) if (tags1_ok(v[i], tag)) pend &= ~(1u << i);
        if (pend == 0) break;
        if (++it > SPIN_LIMIT) __trap();
    }
}
__device__ __forceinline__ void delay_ns(unsigned ns) { if (ns) { const unsigned t0 = gtime(); while (gtime() - t0 < ns) { } } }
__device__ __forceinline__ uint32_t pack_tagged(float lo, float hi, uint32_t tag) {
    uint32_t r0 = __float_as_uint(lo) + 0x10000u;
    uint32_t r1 = __float_as_uint(hi) + 0x8000u;
    return (__byte_perm(r0, r1, 0x7632) & ~1u) | tag;
}
__device__ __forceinline__ uint32_t pack_bf16(float lo, float hi) {
    uint32_t r;
    asm("cvt.rn.bf16x2.f32 %0, %1, %2;" : "=r"(r) : "f"(hi), "f"(lo));
    return r;
}
__device__ __forceinline__ void pace_until(unsigned g0, uint32_t t16) { const unsigned t = t16 >> 4; while (gtime() - g0 < t) { } }
__device__ __forceinline__ void sts64(uint32_t a, uint32_t x, uint32_t y) { asm volatile("st.shared.v2.u32 [%0], {%1,%2};" ::"r"(a), "r"(x), "r"(y) : "memory"); }
__device__ __forceinline__ void hilo2(float v0, float v1, uint32_t& hi, uint32_t& lo) {
    asm("cvt.rn.bf16x2.f32 %0, %1, %2;" : "=r"(hi) : "f"(v1), "f"(v0));
    float r0 = v0 - __uint_as_float(hi << 16), r1 = v1 - __uint_as_float(hi & 0xffff0000u);
    asm("cvt.rn.bf16x2.f32 %0, %1, %2;" : "=r"(lo) : "f"(r1), "f"(r0));
}
__device__ __forceinline__ void sts_hilo(uint32_t a_hi, uint32_t lo_off, float v) {
    __nv_bfloat16 h = __float2bfloat16_rn(v);
    __nv_bfloat16 l = __float2bfloat16_rn(v - __bfloat162float(h));
    sts16(a_hi, __bfloat16_as_ushort(h));
    sts16(a_hi + lo_off, __bfloat16_as_ushort(l));
}
__device__ __forceinline__ float bf16lo(uint32_t w) { return __uint_as_float(w << 16); }
__device__ __forceinline__ float bf16hi(uint32_t w) { return __uint_as_float(w & 0xffff0000u); }
__device__ __forceinline__ float warp_sum(float v) {
#pragma unroll
    for (int o = 16; o; o >>= 1) v += __shfl_xor_sync(0xffffffffu, v, o);
    return v;
}
__device__ __forceinline__ float warp_max(float v) {
#pragma unroll
    for (int o = 16; o; o >>= 1) v = fmaxf(v, __shfl_xor_sync(0xffffffffu, v, o));
    return v;
}

__device__ __forceinline__ uint64_t make_desc(uint32_t addr, uint32_t lbo, uint32_t sbo) {
    return (uint64_t)((addr & 0x3FFFF) >> 4) | ((uint64_t)(lbo >> 4) << 16) | ((uint64_t)(sbo >> 4) << 32) | (1ull << 62);
}
__device__ __forceinline__ uint64_t desc_add(uint64_t d, uint32_t off) { return d + (uint64_t)(off >> 4); }
__device__ __forceinline__ void wg_fence() { asm volatile("wgmma.fence.sync.aligned;" ::: "memory"); }
__device__ __forceinline__ void wg_commit() { asm volatile("wgmma.commit_group.sync.aligned;" ::: "memory"); }
__device__ __forceinline__ void wg_wait0() { asm volatile("wgmma.wait_group.sync.aligned 0;" ::: "memory"); }
template <int TA>
__device__ __forceinline__ void wgmma_n32(float* d, uint64_t da, uint64_t db, int scale_d) {
    asm volatile("{\n.reg .pred p;\nsetp.ne.b32 p, %18, 0;\n"
                 "wgmma.mma_async.sync.aligned.m64n32k16.f32.bf16.bf16 "
                 "{%0,%1,%2,%3,%4,%5,%6,%7,%8,%9,%10,%11,%12,%13,%14,%15}, %16, %17, p, 1, 1, %19, 0;\n}"
                 : "+f"(d[0]), "+f"(d[1]), "+f"(d[2]), "+f"(d[3]), "+f"(d[4]), "+f"(d[5]), "+f"(d[6]), "+f"(d[7]),
                   "+f"(d[8]), "+f"(d[9]), "+f"(d[10]), "+f"(d[11]), "+f"(d[12]), "+f"(d[13]), "+f"(d[14]), "+f"(d[15])
                 : "l"(da), "l"(db), "r"(scale_d), "n"(TA));
}

__device__ __forceinline__ uint32_t bvec_addr(uint32_t base, uint32_t lo_off, uint32_t zero, int lane, int& kstep_bytes) {
    int n = lane & 7, kh = (lane >> 3) & 1;
    if (n < 2) { kstep_bytes = 32; return base + n * lo_off + kh * 16; }
    kstep_bytes = 0;
    return zero;
}

template <int NP>
__device__ __forceinline__ float cta_reduce32(const uint4* part, uint32_t red, uint32_t tag, int warp, int lane, uint32_t sb = 0, int dbg = 0) {
    constexpr int NI = NP / 32;
    const uint4* src = part + (warp * (NP / 8) + (lane >> 3)) * 8 + (lane & 7);
    uint4 v[NI];
    uint32_t pend = (1u << NI) - 1u;
    int it = 0;
    while (true) {
#pragma unroll
        for (int k = 0; k < NI; k++) if (pend & (1u << k)) v[k] = ld_relaxed4(src + k * 32);
#pragma unroll
        for (int k = 0; k < NI; k++) if (tags_ok(v[k], tag)) pend &= ~(1u << k);
        if (__all_sync(0xffffffffu, pend == 0)) break;
        if (++it > SPIN_LIMIT) __trap();
    }
    float x0 = 0.f, x1 = 0.f, x2 = 0.f, x3 = 0.f;
#pragma unroll
    for (int k = 0; k < NI; k++) { x0 += untag(v[k].x); x1 += untag(v[k].y); x2 += untag(v[k].z); x3 += untag(v[k].w); }
    const bool b4 = lane & 16, b3 = lane & 8;
    const float t0 = (b4 ? x2 : x0) + __shfl_xor_sync(0xffffffffu, b4 ? x0 : x2, 16);
    const float t1 = (b4 ? x3 : x1) + __shfl_xor_sync(0xffffffffu, b4 ? x1 : x3, 16);
    const float s0 = (b3 ? t1 : t0) + __shfl_xor_sync(0xffffffffu, b3 ? t0 : t1, 8);
    stsf(red + (warp * 32 + 4 * (lane & 7) + 2 * (lane >> 4) + ((lane >> 3) & 1)) * 4, s0);
    nbar_sync(NB_CMP, 256);
    float t = 0.f;
#pragma unroll
    for (int w = 0; w < 8; w++) t += ldsf(red + (w * 32 + lane) * 4);
    return t;
}

template <int KSTEPS>
__device__ __forceinline__ void frag576_load(uint32_t (*af)[2][KSTEPS][4], uint32_t tile, int warp, int lane) {
    const int mi = lane >> 3, r8 = lane & 7;
    const uint32_t base = tile + (mi >> 1) * 9216 + (warp >> 1) * 1024 + r8 * 128;
    const int cc = (warp & 1) * 4 + (mi & 1);
    const uint32_t a0 = base + ((cc ^ r8) << 4), a1 = base + (((cc + 2) ^ r8) << 4);
#pragma unroll
    for (int pi = 0; pi < 3; pi++) {
        if (pi < 2 || warp < 2) {
#pragma unroll
            for (int s = 0; s < KSTEPS; s++) {
                ldsm4t(a0 + pi * 4096 + s * 18432, af[pi][0][s][0], af[pi][0][s][1], af[pi][0][s][2], af[pi][0][s][3]);
                ldsm4t(a1 + pi * 4096 + s * 18432, af[pi][1][s][0], af[pi][1][s][1], af[pi][1][s][2], af[pi][1][s][3]);
            }
        }
    }
}
template <int KSTEPS>
__device__ __forceinline__ void gemv576_finish(uint32_t (*af)[2][KSTEPS][4], uint32_t vec, uint32_t lo_off, uint32_t zero, uint4* part, int b,
                                               uint32_t tag, int warp, int lane) {
    int kb; uint32_t ba = bvec_addr(vec, lo_off, zero, lane, kb);
    uint32_t bf[KSTEPS][2];
#pragma unroll
    for (int s = 0; s < KSTEPS; s++) ldsm2(ba + s * kb, bf[s][0], bf[s][1]);
    float acc[3][2][4] = {};
#pragma unroll
    for (int s = 0; s < KSTEPS; s++)
#pragma unroll
        for (int pi = 0; pi < 3; pi++)
            if (pi < 2 || warp < 2) {
#pragma unroll
                for (int tl = 0; tl < 2; tl++)
                    mma16816(acc[pi][tl], af[pi][tl][s][0], af[pi][tl][s][1], af[pi][tl][s][2], af[pi][tl][s][3], bf[s][0], bf[s][1]);
            }
    const int src = lane & ~3, q = lane & 3;
    uint32_t* dst = (uint32_t*)part + (warp * 128 + b) * 32 + 8 * q + (lane >> 2);
#pragma unroll
    for (int pi = 0; pi < 3; pi++)
        if (pi < 2 || warp < 2) {
            const float v0 = __shfl_sync(0xffffffffu, acc[pi][0][0] + acc[pi][0][1], src), v1 = __shfl_sync(0xffffffffu, acc[pi][0][2] + acc[pi][0][3], src);
            const float v2 = __shfl_sync(0xffffffffu, acc[pi][1][0] + acc[pi][1][1], src), v3 = __shfl_sync(0xffffffffu, acc[pi][1][2] + acc[pi][1][3], src);
            xchg_word(dst + pi * (8 * 128 * 32), tagf(q == 0 ? v0 : q == 1 ? v1 : q == 2 ? v2 : v3, tag));
        }
}

__global__ void __cluster_dims__(2, 1, 1) __launch_bounds__(NTHREADS, 1)
fused_decode_kernel(const __grid_constant__ CUtensorMap tm_op, const __grid_constant__ CUtensorMap tm_st, const __grid_constant__ CUtensorMap tm_wuk, const __grid_constant__ CUtensorMap tm_ckv, const __grid_constant__ CUtensorMap tm_wuv,
                    const __grid_constant__ CUtensorMap tm_wo, const __grid_constant__ CUtensorMap tm_w1,
                    const __grid_constant__ CUtensorMap tm_w2, const Params prm)
{
    extern __shared__ uint8_t smem_raw[];
    const uint32_t sb = (smem_u32(smem_raw) + 1023u) & ~1023u;
    const int tid = threadIdx.x, warp = tid >> 5, lane = tid & 31;
    const int b = blockIdx.x;
    const uint32_t bars = sb + R_BAR;
    const uint32_t zero = sb + R_ZERO;
    auto BAR = [&](int i) { return bars + 8u * i; };

    const unsigned g0 = gtime();
    if (tid == 0) TS(0);
    uint32_t xw[9];
    unsigned epoch = 0;
    const __nv_bfloat16* wq_src = prm.wq + (size_t)(32 * (b & 1) + (tid >> 3)) * 4096 + (b >> 1) * 64 + (tid & 7) * 8;
    const uint32_t wq_off = (tid >> 3) * 128 + (((tid & 7) ^ ((tid >> 3) & 7)) << 4);
    if (warp < 8) {
        if (!PF_AHEAD) cp_async16(sb + R_A + wq_off, wq_src);
        if (tid < 144) {
            if (b < NFFN) st_relaxed4(g_pE8 + ((tid >> 3) * 128 + b) * 8 + (tid & 7), 0, 0, 0, 0);
            if (tid < ((b & 1) ? 64 : 80)) st_relaxed4(g_pE6 + (((tid >> 3) + 10 * (b & 1)) * 64 + (b >> 1)) * 8 + (tid & 7), 0, 0, 0, 0);
        }
        else if (!E4_LL && tid >= 160 && tid < 160 + 2 * FREP) st_relaxed4(g_flagB + (((tid - 160) >> 1) * 128 + b) * 2 + (tid & 1), 0, 0, 0, 0);
        else if (tid >= 184 && tid < 192) st_relaxed4(g_xq + b * 8 + (tid - 184), 0, 0, 0, 0);
#pragma unroll 1
        for (int i = PF_AHEAD ? 0 : 1; i < 9; i++) {
            pace_until(g0, START_OFF * 16 + i * pace16(4096) + (PF_AHEAD ? LAG0_NS * 16 : 0));
            cp_async16(sb + R_A + i * 4096 + wq_off, wq_src + (size_t)i * 64 * 4096);
        }
    } else if (warp == 9) {
        epoch = ld_relaxed(&g_epoch);
#pragma unroll
        for (int i = 0; i < 9; i++) xw[i] = __ldg((const uint32_t*)prm.x + lane + 32 * i);
        if (lane < 4) sts32(zero + 4 * lane, 0u);
    } else {
        if (lane == 0) {
            const int i0 = warp == 8 ? 0 : (warp == 10 ? 6 : 12);
            const int i1 = warp == 8 ? 6 : (warp == 10 ? 12 : NBAR);
#pragma unroll 1
            for (int i = i0; i < i1; i++) {
                const uint32_t cnt = i == B_WQ ? 256u : (POLICY == 3 && i == B_W1) ? 32u : ((i == B_FREEC || i == B_E4 || i == B_FS) ? 8u : (i == B_FREEA ? 4u : 1u));
                mbar_init(BAR(i), cnt);
                const uint32_t tx = i == B_WUK ? 32768u : (i >= B_CKV0 && i <= B_CKV3) ? 16384u : i == B_WUV ? 32768u
                                  : i == B_WO ? ((b & 1) ? 32768u : 40960u) : i == B_W1 ? (POLICY == 3 ? 0u : 55296u) : i == B_W2 ? 55296u : (i == B_XQ || i == B_XC) ? 512u : i == B_QA ? 32768u : (i == B_ST || i == B_SL) ? 128u : i == B_IN ? 16384u : 0u;
                if (tx) mbar_expect_tx(BAR(i), tx);
            }
            asm volatile("fence.mbarrier_init.release.cluster;" ::: "memory");
            fence_async_smem();
        }
        if (warp == 8) {
            if (lane < 8) {
                const CUtensorMap* t = lane == 7 ? &tm_st : lane == 0 ? &tm_ckv : lane == 1 ? &tm_wuv : lane == 2 ? &tm_wo : lane == 3 ? &tm_w1 : lane == 4 ? &tm_w2 : lane == 5 ? &tm_wuk : &tm_op;
                prefetch_tmap(t);
            }
        } else {
            epoch = ld_relaxed(&g_epoch);
            if (b >= NFFN && b < NFFN + 18 && warp == 10) st_relaxed4((uint32_t*)g_hbuf + (lane >> 3) * 576 + 32 * (b - NFFN) + (lane & 7) * 4, 0, 0, 0, 0);
        }
    }
    float ln_mean = 0.f, ln_rstd = 0.f;
    if (warp == 9) {
        float sum = 0.f;
#pragma unroll
        for (int i = 0; i < 9; i++) sum += bf16lo(xw[i]) + bf16hi(xw[i]);
        ln_mean = warp_sum(sum) * (1.f / 576.f);
        float sq = 0.f;
#pragma unroll
        for (int i = 0; i < 9; i++) { float a = bf16lo(xw[i]) - ln_mean, c = bf16hi(xw[i]) - ln_mean; sq += a * a + c * c; }
        ln_rstd = rsqrtf(warp_sum(sq) * (1.f / 576.f) + 1e-5f);
#pragma unroll
        for (int i = 0; i < 9; i++) {
            const int m = 2 * (lane + 32 * i);
            const int e = 32 * (m >> 6) + (m & 31);
            if (((m >> 5) & 1) == (b & 1)) {
                uint32_t hi, lo;
                hilo2((bf16lo(xw[i]) - ln_mean) * ln_rstd, (bf16hi(xw[i]) - ln_mean) * ln_rstd, hi, lo);
                sts32(sb + R_VXN + e * 2, hi);
                sts32(sb + R_VXN + VXN_LO + e * 2, lo);
            }
        }
        if (lane == 0) { sts32(sb + R_TAG, (epoch + 1u) & 1u); sts32(sb + R_TAG + 4, epoch + 1u); }
    }
    if (warp == 10) nbar_arrive(NB_INIT, NTHREADS); else nbar_sync(NB_INIT, NTHREADS);
    asm volatile("barrier.cluster.arrive.relaxed.aligned;" ::: "memory");
    if (warp == 10 && lane == 0 && PF_AHEAD) {
#pragma unroll 1
        for (int k = 0; k < 17; k++) {
            pace_until(g0, START_OFF * 16 + k * pace16(4096));
            l2_prefetch(k < 9 ? (const char*)prm.wq + (size_t)(k * 128 + b) * 4096 : prm.wuk + (size_t)((k - 9) * 128 + b) * 4096, 4096);
        }
    }

    if (warp < 8) {
        const int mi = lane >> 3, r8 = lane & 7, q4 = lane & 3, g8 = lane >> 2;
        cp_async_arrive(BAR(B_WQ));
        const uint32_t tag = lds32(sb + R_TAG);
        if (warp == 0 && lane < 16)
            st_relaxed4((char*)g_qabs + (2 * (b & 3) + (lane >> 3)) * 4096 + (b >> 2) * 128 + (lane & 7) * 16, tag ^ 1u, 0, 0, 0);
        {
            const int mt = warp & 3, kh = warp >> 2;
            const uint32_t aa = sb + R_A + (144 * kh + (mi >> 1) * 8 + r8) * 128 + (((2 * mt + (mi & 1)) ^ r8) << 4);
            int kb; uint32_t ba = bvec_addr(sb + R_VXN + kh * 288, VXN_LO, zero, lane, kb);
            uint32_t bf[9][2];
#pragma unroll
            for (int s = 0; s < 9; s++) ldsm2(ba + s * kb, bf[s][0], bf[s][1]);
            mbar_wait(BAR(B_WQ));
            if (tid == 0) TS(1);
            float acc[3][4] = {};
#pragma unroll
            for (int s = 0; s < 9; s++) {
                uint32_t a0, a1, a2, a3;
                ldsm4t(aa + s * 2048, a0, a1, a2, a3);
                mma16816(acc[s % 3], a0, a1, a2, a3, bf[s][0], bf[s][1]);
            }
            const float v0 = (acc[0][0] + acc[0][1]) + (acc[1][0] + acc[1][1]) + (acc[2][0] + acc[2][1]);
            const float v1 = (acc[0][2] + acc[0][3]) + (acc[1][2] + acc[1][3]) + (acc[2][2] + acc[2][3]);
            asm volatile("barrier.cluster.wait.acquire.aligned;" ::: "memory");
            const uint32_t xq = sb + R_XQP + (kh * 64 + mt * 16 + g8) * 4;
            if (q4 == 0) {
                const uint32_t rq = mapa(xq + 512, (b & 1) ^ 1), rb = mapa(BAR(B_XQ), (b & 1) ^ 1);
                st_async_f32(rq, v0, rb);
                st_async_f32(rq + 32, v1, rb);
                stsf(xq, v0); stsf(xq + 32, v1);
            }
            if (tid == 0) TS(2);
        }
        {
            const int h = b >> 2;
            const int row = 16 * warp + (mi & 1) * 8 + r8;
            const uint32_t aa = sb + R_A + R_A_WUK + (row >> 5) * 8192 + (row & 31) * 128;
            uint32_t af[8][4];
            nbar_sync(NB_CMP, 256);
            mbar_wait_cluster(BAR(B_XQ));
            if (warp < 2) {
                const uint32_t xq = sb + R_XQP + tid * 4;
                const float qv = (ldsf(xq) + ldsf(xq + 256)) + (ldsf(xq + 512) + ldsf(xq + 768));
                if (warp == (b & 1)) xchg_word((uint32_t*)g_xq + b * 32 + lane, tagf(qv, tag));
                sts_hilo(sb + R_VQ + (64 * ((b >> 1) & 1) + tid) * 2, VQ_LO, qv);
            } else if (warp == 2) {
                const uint2* src = (const uint2*)(g_xq + ((b & ~3) + ((b & 2) ^ 2)) * 8) + lane;
                uint2 v; int it = 0; bool ok = false;
                while (true) {
                    if (!ok) { v = ld_relaxed2(src); ok = (((v.x ^ (tag | 2u)) | (v.y ^ (tag | 2u))) & 3u) == 0; }
                    if (__all_sync(0xffffffffu, ok)) break;
                    if (++it > SPIN_LIMIT) __trap();
                }
                uint32_t hi, lo;
                hilo2(untag(v.x), untag(v.y), hi, lo);
                const uint32_t a = sb + R_VQ + (64 * (((b >> 1) & 1) ^ 1) + 2 * lane) * 2;
                sts32(a, hi); sts32(a + VQ_LO, lo);
            }
            mbar_wait(BAR(B_WUK));
#pragma unroll
            for (int s = 0; s < 8; s++) {
                const int cc = (s & 3) * 2 + (mi >> 1);
                ldsm4(aa + (s >> 2) * 4096 + ((cc ^ r8) << 4), af[s][0], af[s][1], af[s][2], af[s][3]);
            }
            nbar_sync(NB_CMP, 256);
            if (tid == 0) TS(3);
            int kb; uint32_t ba = bvec_addr(sb + R_VQ, VQ_LO, zero, lane, kb);
            float acc[2][4] = {};
#pragma unroll
            for (int s = 0; s < 8; s++) {
                uint32_t b0, b1;
                ldsm2(ba + s * kb, b0, b1);
                mma16816(acc[s & 1], af[s][0], af[s][1], af[s][2], af[s][3], b0, b1);
            }
            const float sc = 0.08838834764831845f * 1.4426950408889634f;
            const float v0 = ((acc[0][0] + acc[0][1]) + (acc[1][0] + acc[1][1])) * sc;
            const float v1 = ((acc[0][2] + acc[0][3]) + (acc[1][2] + acc[1][3])) * sc;
            if (q4 == 0) {
                const uint32_t st = sb + R_RED + (warp >> 2) * 128 + g8 * 2;
                const int c0 = ((warp & 3) * 2) ^ (h & 7), c1 = c0 ^ 1;
                uint32_t w0 = __bfloat16_as_ushort(__float2bfloat16_rn(v0)), w1 = __bfloat16_as_ushort(__float2bfloat16_rn(v1));
                if (g8 == 0) {
                    if ((c0 & 1) == 0) w0 = (((__float_as_uint(v0) + 0x10000u) >> 16) & 0xfffeu) | tag;
                    else w1 = (((__float_as_uint(v1) + 0x10000u) >> 16) & 0xfffeu) | tag;
                }
                sts16(st + (c0 << 4), (uint16_t)w0);
                sts16(st + (c1 << 4), (uint16_t)w1);
            }
        }
        nbar_sync(NB_CMP, 256);
        const uint32_t fval = lds32(sb + R_TAG + 4);
        if (warp == 0 && lane < 16) {
            const uint4 v = lds128(sb + R_RED + lane * 16);
            st_relaxed4((char*)g_qabs + (2 * (b & 3) + (lane >> 3)) * 4096 + (b >> 2) * 128 + (lane & 7) * 16, v.x, v.y, v.z, v.w);
        }
        if (tid == 0) {
            TS(4);
            delay_ns(DELAY_E2);
            TS(5);
            const uint32_t half = (b & 1) * 16384;
            asm volatile("cp.async.bulk.shared::cluster.global.mbarrier::complete_tx::bytes.multicast::cluster [%0], [%1], 16384, [%2], %3;"
                         ::"r"(sb + R_A + half), "l"((const char*)g_qabs + half), "r"(BAR(B_QA)), "h"((uint16_t)3) : "memory");
        }
        mbar_wait(BAR(B_QA));
        {
#pragma unroll
            for (int i = 0; i < 4; i++) {
                const uint32_t off = (tid + 256 * i) * 32;
                uint32_t w = lds32(sb + R_A + off);
                if ((w & 1u) != tag) {
                    int it = 0;
                    uint4 x, y;
                    do { x = ld_relaxed4((const char*)g_qabs + off); y = ld_relaxed4((const char*)g_qabs + off + 16); if (++it > SPIN_LIMIT) __trap(); } while ((x.x & 1u) != tag);
                    sts128(sb + R_A + off, x.x, x.y, x.z, x.w); sts128(sb + R_A + off + 16, y.x, y.y, y.z, y.w);
                    w = x.x;
                }
                sts32(sb + R_A + off, w & ~1u);
            }
        }
        fence_async_smem();
        nbar_sync(NB_CMP, 256);
        if (tid == 0) TS(6);
        float mx[8], sum[8];
        if (E4_LL && warp >= 4) {
            const uint32_t inv = tag ^ 1u;
#pragma unroll
            for (int i = 0; i < 8; i++) sts128(sb + R_INBOX + (i * 128 + (tid & 127)) * 16, inv, inv, inv, inv);
            if (tid < 128 + 8) sts128(sb + R_STST + (tid - 128) * 16, 0, 0, 0, 0);
            fence_async_smem();
            nbar_sync(NB_G2, 128);
            if (tid == 128) {
                asm volatile("cp.async.bulk.tensor.4d.global.shared::cta.tile.bulk_group [%0, {%1, %2, %3, %4}], [%5];"
                             ::"l"(&tm_op), "r"(0), "r"(b >> 1), "r"(b & 1), "r"(0), "r"(sb + R_INBOX) : "memory");
                asm volatile("cp.async.bulk.tensor.4d.global.shared::cta.tile.bulk_group [%0, {%1, %2, %3, %4}], [%5];"
                             ::"l"(&tm_st), "r"(0), "r"(b >> 1), "r"(b & 1), "r"(0), "r"(sb + R_STST) : "memory");
                asm volatile("cp.async.bulk.commit_group;" ::: "memory");
                asm volatile("cp.async.bulk.wait_group.read 0;" ::: "memory");
                mbar_arrive(BAR(B_RST));
                asm volatile("cp.async.bulk.wait_group 0;" ::: "memory");
            }
        }
        if (warp < 4) {
            float s4[4][16];
#pragma unroll
            for (int a = 0; a < 4; a++)
#pragma unroll
                for (int i = 0; i < 16; i++) s4[a][i] = 0.f;
            const uint64_t da0 = make_desc(sb + R_C, 16, CKV_GS), db0 = make_desc(sb + R_A, 16, 1024);

            if (CKV_CONTIG) { mbar_wait(BAR(B_CKV0)); mbar_wait(BAR(B_CKV1)); mbar_wait(BAR(B_CKV2)); }
#pragma unroll
            for (int k = 0; k < 4; k++) {
                if (!CKV_CONTIG || k == 0) mbar_wait(BAR(CKV_CONTIG ? B_CKV3 : B_CKV0 + k));
                wg_fence();
#pragma unroll
                for (int u = 0; u < 8; u++) {
                    const int blk = 2 * k + (u >> 2), ks = u & 3;
                    wgmma_n32<0>(s4[ks], desc_add(da0, blk * CKV_BS + ks * 32), desc_add(db0, blk * 4096 + ks * 32), (k | (u >> 2)) != 0);
                }
                wg_commit();
            }
            wg_wait0();
            float s[16];
#pragma unroll
            for (int i = 0; i < 16; i++) s[i] = (s4[0][i] + s4[1][i]) + (s4[2][i] + s4[3][i]);
            if (lane == 0) mbar_arrive(BAR(B_FREEA));
            if (tid == 0) TS(7);
#pragma unroll
            for (int i = 0; i < 4; i++) {
                mx[2 * i] = fmaxf(s[4 * i], s[4 * i + 2]);
                mx[2 * i + 1] = fmaxf(s[4 * i + 1], s[4 * i + 3]);
            }
#pragma unroll
            for (int o = 4; o <= 16; o <<= 1)
#pragma unroll
                for (int i = 0; i < 8; i++) mx[i] = fmaxf(mx[i], __shfl_xor_sync(0xffffffffu, mx[i], o));
            if (g8 == 0) {
#pragma unroll
                for (int i = 0; i < 4; i++) {
                    stsf(sb + R_SMAX + (warp * 32 + 8 * i + 2 * q4) * 4, mx[2 * i]);
                    stsf(sb + R_SMAX + (warp * 32 + 8 * i + 2 * q4 + 1) * 4, mx[2 * i + 1]);
                }
            }
            nbar_sync(NB_WG0, 128);
#pragma unroll
            for (int i = 0; i < 4; i++) {
                float2 m0 = ldsf2(sb + R_SMAX + (0 * 32 + 8 * i + 2 * q4) * 4), m1 = ldsf2(sb + R_SMAX + (1 * 32 + 8 * i + 2 * q4) * 4);
                float2 m2 = ldsf2(sb + R_SMAX + (2 * 32 + 8 * i + 2 * q4) * 4), m3 = ldsf2(sb + R_SMAX + (3 * 32 + 8 * i + 2 * q4) * 4);
                mx[2 * i] = fmaxf(fmaxf(m0.x, m1.x), fmaxf(m2.x, m3.x));
                mx[2 * i + 1] = fmaxf(fmaxf(m0.y, m1.y), fmaxf(m2.y, m3.y));
            }
            if (E4_LL && warp == 0) mbar_wait(BAR(B_RST));
            if (warp == 0 && g8 == 0) {
                const uint32_t peer = (b & 1) ^ 1, rb = mapa(BAR(B_ST), peer);
#pragma unroll
                for (int i = 0; i < 8; i++) {
                    const uint32_t a = sb + R_ST + (8 * (i >> 1) + 2 * q4 + (i & 1)) * 4;
                    stsf(a, mx[i]);
                    st_async_f32(mapa(a + 256, peer), mx[i], rb);
                }
            }
            uint32_t pk[8];
#pragma unroll
            for (int i = 0; i < 4; i++) {
                uint32_t w0 = pack_bf16(ex2(s[4 * i] - mx[2 * i]), ex2(s[4 * i + 1] - mx[2 * i + 1]));
                uint32_t w1 = pack_bf16(ex2(s[4 * i + 2] - mx[2 * i]), ex2(s[4 * i + 3] - mx[2 * i + 1]));
                pk[i] = w0; pk[4 + i] = w1;
                sum[2 * i] = bf16lo(w0) + bf16lo(w1);
                sum[2 * i + 1] = bf16hi(w0) + bf16hi(w1);
            }
            const int head = lane;
            uint32_t a = sb + R_P + head * 128;
            stsm4t(a + (((2 * warp) ^ (head & 7)) << 4), pk[0], pk[1], pk[2], pk[3]);
            stsm4t(a + (((2 * warp + 1) ^ (head & 7)) << 4), pk[4], pk[5], pk[6], pk[7]);
            fence_async_smem();
        }
        nbar_sync(NB_CMP, 256);
        if (tid == 0) TS(8);
        {
            const int wg = __shfl_sync(0xffffffffu, warp >> 2, 0), w = warp & 3;
            const int rk = b & 1;
            const uint64_t db0 = make_desc(sb + R_P, 16, 1024);
            const uint64_t das = make_desc(sb + R_C + (4 * (rk ^ 1) + 2 * wg) * CKV_BS, CKV_GS, CKV_GS);
            const uint64_t dak = make_desc(sb + R_C + (4 * rk + 2 * wg) * CKV_BS, CKV_GS, CKV_GS);
            float os[2][16], ok_[2][16];
            wg_fence();
#pragma unroll
            for (int ks = 0; ks < 4; ks++)
#pragma unroll
                for (int t = 0; t < 2; t++) wgmma_n32<1>(os[t], desc_add(das, t * CKV_BS + ks * 2 * CKV_GS), desc_add(db0, ks * 32), ks != 0);
            wg_commit();
#pragma unroll
            for (int ks = 0; ks < 4; ks++)
#pragma unroll
                for (int t = 0; t < 2; t++) wgmma_n32<1>(ok_[t], desc_add(dak, t * CKV_BS + ks * 2 * CKV_GS), desc_add(db0, ks * 32), ks != 0);
            wg_commit();
            if (warp < 4) {
#pragma unroll
                for (int of = 4; of <= 16; of <<= 1)
#pragma unroll
                    for (int i = 0; i < 8; i++) sum[i] += __shfl_xor_sync(0xffffffffu, sum[i], of);
                if (g8 == 0) {
#pragma unroll
                    for (int i = 0; i < 4; i++) {
                        stsf(sb + R_SSUM + (warp * 32 + 8 * i + 2 * q4) * 4, sum[2 * i]);
                        stsf(sb + R_SSUM + (warp * 32 + 8 * i + 2 * q4 + 1) * 4, sum[2 * i + 1]);
                    }
                }
                nbar_sync(NB_WG0, 128);
                if (warp == 0) {
                    const uint32_t a = sb + R_SSUM + lane * 4;
                    const float l = (ldsf(a) + ldsf(a + 128)) + (ldsf(a + 256) + ldsf(a + 384));
                    const uint32_t d = sb + R_ST + 128 + lane * 4, peer = rk ^ 1;
                    stsf(d, l);
                    st_async_f32(mapa(d + 256, peer), l, mapa(BAR(B_SL), peer));
                }
            }
            mbar_wait_cluster(BAR(B_ST));
            float f[8];
#pragma unroll
            for (int i = 0; i < 4; i++) {
                const float2 mo = ldsf2(sb + R_ST + (8 * i + 2 * q4) * 4), mp = ldsf2(sb + R_ST + 256 + (8 * i + 2 * q4) * 4);
                f[2 * i] = ex2(mo.x - fmaxf(mo.x, mp.x)); f[2 * i + 1] = ex2(mo.y - fmaxf(mo.y, mp.y));
            }
            asm volatile("wgmma.wait_group.sync.aligned 1;" ::: "memory");
            {
                const uint32_t peer = rk ^ 1, dst = mapa(sb + R_INBOX + tid * 16, peer), rb = mapa(BAR(B_IN), peer);
#pragma unroll
                for (int t = 0; t < 2; t++)
#pragma unroll
                    for (int ih = 0; ih < 2; ih++) {
                        uint32_t wd[4];
#pragma unroll
                        for (int k = 0; k < 4; k++) {
                            const int i = 2 * ih + (k >> 1), e = k & 1;
                            wd[k] = pack_bf16(os[t][4 * i + e] * f[2 * i + e], os[t][4 * i + 2 + e] * f[2 * i + e]);
                        }
                        st_async_v4(dst + (2 * t + ih) * 4096, wd[0], wd[1], wd[2], wd[3], rb);
                    }
            }
            wg_wait0();
            if (lane == 0) mbar_arrive(BAR(B_FREEC));
            if (tid == 0) TS(9);
            if (warp == 7) {
                nbar_sync(NB_G2, 64);
                mbar_wait_cluster(BAR(B_SL));
                const uint32_t a = sb + R_ST + lane * 4;
                const float mo = ldsf(a), lo = ldsf(a + 128), mp = ldsf(a + 256), lp = ldsf(a + 384), m = fmaxf(mo, mp);
                if (((lane >> 2) & 1) == rk)
                    sts64(sb + R_STST + (lane >> 3) * 32 + (lane & 3) * 8, tagf(m, tag), tagf(lo * ex2(mo - m) + lp * ex2(mp - m), tag));
            } else if (warp == 0) nbar_arrive(NB_G2, 64);
            mbar_wait_cluster(BAR(B_IN));
            uint4 pv[4];
#pragma unroll
            for (int j = 0; j < 4; j++) pv[j] = lds128(sb + R_INBOX + j * 4096 + tid * 16);
            nbar_sync(NB_CMP, 256);
#pragma unroll
            for (int t = 0; t < 2; t++)
#pragma unroll
                for (int ih = 0; ih < 2; ih++) {
                    const uint32_t wd[4] = {pv[2 * t + ih].x, pv[2 * t + ih].y, pv[2 * t + ih].z, pv[2 * t + ih].w};
#pragma unroll
                    for (int k = 0; k < 4; k++) {
                        const int i = 2 * ih + (k >> 1), e = k & 1;
                        sts32(sb + R_INBOX + (8 * i + 2 * q4 + e) * 512 + ((2 * wg + t) * 32 + ((w + q4) & 3) * 8 + g8) * 4,
                              pack_tagged(fmaf(ok_[t][4 * i + e], f[2 * i + e], bf16lo(wd[k])), fmaf(ok_[t][4 * i + 2 + e], f[2 * i + e], bf16hi(wd[k])), tag));
                    }
                }
            fence_async_smem();
            nbar_arrive(NB_G3, 288);
            mbar_wait(BAR(B_WUV));
        }
        if (tid == 0) TS(10);
        uint32_t cf[8][4];
        {
            const int h = b >> 2;
            {
                const uint32_t aa = sb + R_V + (128 * (warp >> 2) + (mi >> 1) * 8 + r8) * 128 + (((2 * (warp & 3) + (mi & 1)) ^ r8) << 4);
#pragma unroll
                for (int s = 0; s < 8; s++) ldsm4t(aa + s * 2048, cf[s][0], cf[s][1], cf[s][2], cf[s][3]);
            }
            uint4 v[8]; uint2 st[8];
            {
                bool ok = lane >= 8;
                const uint32_t* fl = (const uint32_t*)(g_flagB + ((b & (FREP - 1)) * 128 + 2 * (warp * 8 + (lane & 7)) + (b & 1)) * 2);
                const uint32_t* fl2 = (const uint32_t*)(g_flagB + ((b & (FREP - 1)) * 128 + 2 * (warp * 8 + (lane & 7)) + ((h >> 2) & 1)) * 2);
                bool ok2 = lane >= 8;
                int it = 0;
                while (true) {
                    if (!ok) ok = ld_relaxed(fl) == fval;
                    if (!ok2) ok2 = ld_relaxed(fl2) == fval;
                    if (__all_sync(0xffffffffu, ok && ok2)) break;
                    if (++it > SPIN_LIMIT) __trap();
                }
            }
            if (lane == 0) mbar_arrive(BAR(B_FS));
            if (tid == 0) TS(15);
            {
                const uint4* src = g_opart + ((size_t)(2 * h + (b & 1)) * 64 + warp * 8) * 32 + lane;
                const uint2* ssrc = (const uint2*)g_stats + ((h >> 2) * 64 + warp * 8) * 4 + (h & 3);
                int it = 0;
                while (true) {
#pragma unroll
                    for (int r = 0; r < 8; r++) { v[r] = ld_relaxed4(src + r * 32); st[r] = ld_relaxed2(ssrc + r * 4); }
                    bool ok = true;
#pragma unroll
                    for (int r = 0; r < 8; r++) ok = ok && tags1_ok(v[r], tag) && (((st[r].x ^ (tag | 2u)) | (st[r].y ^ (tag | 2u))) & 3u) == 0;
                    if (__all_sync(0xffffffffu, ok)) break;
                    if (++it > SPIN_LIMIT) __trap();
                }
            }
            if (lane == 0) mbar_arrive(BAR(B_E4));
            if (tid == 0) TS(11);
            float m = untag(st[0].x);
#pragma unroll
            for (int r = 1; r < 8; r++) m = fmaxf(m, untag(st[r].x));
            float acc[8] = {}, l = 0.f;
#pragma unroll
            for (int r = 0; r < 8; r++) {
                const float wt = ex2(untag(st[r].x) - m);
                l = fmaf(wt, untag(st[r].y), l);
                acc[0] = fmaf(wt, bf16lo(v[r].x & ~1u), acc[0]); acc[1] = fmaf(wt, bf16hi(v[r].x), acc[1]);
                acc[2] = fmaf(wt, bf16lo(v[r].y & ~1u), acc[2]); acc[3] = fmaf(wt, bf16hi(v[r].y), acc[3]);
                acc[4] = fmaf(wt, bf16lo(v[r].z & ~1u), acc[4]); acc[5] = fmaf(wt, bf16hi(v[r].z), acc[5]);
                acc[6] = fmaf(wt, bf16lo(v[r].w & ~1u), acc[6]); acc[7] = fmaf(wt, bf16hi(v[r].w), acc[7]);
            }
            {
                const uint32_t a = sb + R_P + warp * 1024 + lane * 16;
                sts128(a, __float_as_uint(acc[0]), __float_as_uint(acc[1]), __float_as_uint(acc[2]), __float_as_uint(acc[3]));
                sts128(a + 512, __float_as_uint(acc[4]), __float_as_uint(acc[5]), __float_as_uint(acc[6]), __float_as_uint(acc[7]));
                if (lane == 0) sts64(sb + R_WTS + warp * 8, __float_as_uint(m), __float_as_uint(l));
            }
            nbar_sync(NB_CMP, 256);
            {
                float2 ml[8];
                float M = -INFINITY;
#pragma unroll
                for (int w = 0; w < 8; w++) { ml[w] = ldsf2(sb + R_WTS + w * 8); M = fmaxf(M, ml[w].x); }
                float sacc = 0.f, L = 0.f;
#pragma unroll
                for (int w = 0; w < 8; w++) {
                    const float sc = ex2(ml[w].x - M);
                    L = fmaf(sc, ml[w].y, L);
                    sacc = fmaf(sc, ldsf(sb + R_P + w * 1024 + tid * 4), sacc);
                }
                const int u = (tid >> 2) & 31, k = 4 * (tid >> 7) + (tid & 3), pos = 4 * u + (k >> 1);
                const int c = 64 * (pos >> 5) + 16 * ((((pos >> 3) & 3) - (h >> 1)) & 3) + (pos & 7) + 8 * (k & 1);
                sts_hilo(sb + R_VO + c * 2, VO_LO, __fdividef(sacc, L));
            }
            nbar_sync(NB_CMP, 256);
        }
        if (tid == 0) TS(12);
        {
            int kb; uint32_t ba = bvec_addr(sb + R_VO + (warp >> 2) * 256, VO_LO, zero, lane, kb);
            float acc[2][4] = {};
#pragma unroll
            for (int s = 0; s < 8; s++) {
                uint32_t b0, b1;
                ldsm2(ba + s * kb, b0, b1);
                mma16816(acc[s & 1], cf[s][0], cf[s][1], cf[s][2], cf[s][3], b0, b1);
            }
            if (q4 == 0) {
                const float v0 = (acc[0][0] + acc[0][1]) + (acc[1][0] + acc[1][1]), v1 = (acc[0][2] + acc[0][3]) + (acc[1][2] + acc[1][3]);
                const uint32_t xq = sb + R_XQP + ((warp >> 2) * 64 + (warp & 3) * 16 + g8) * 4;
                const uint32_t rq = mapa(xq + 512, (b & 1) ^ 1), rb = mapa(BAR(B_XC), (b & 1) ^ 1);
                st_async_f32(rq, v0, rb);
                st_async_f32(rq + 32, v1, rb);
                stsf(xq, v0); stsf(xq + 32, v1);
            }
        }
        if (tid == 0) TS(14);
        {
            uint32_t af[2][2][4][4];
            const bool two = (b & 1) == 0 && warp < 2;
            mbar_wait(BAR(B_WO));
            {
                const uint32_t base = sb + R_O + (warp >> 1) * 8192 + ((mi >> 1) * 8 + r8) * 128;
                const int cc = (warp & 1) * 4 + (mi & 1);
                const uint32_t a0 = base + ((cc ^ r8) << 4), a1 = base + (((cc + 2) ^ r8) << 4);
#pragma unroll
                for (int pi = 0; pi < 2; pi++)
                    if (pi == 0 || two) {
#pragma unroll
                        for (int s = 0; s < 4; s++) {
                            ldsm4t(a0 + pi * 32768 + s * 2048, af[pi][0][s][0], af[pi][0][s][1], af[pi][0][s][2], af[pi][0][s][3]);
                            ldsm4t(a1 + pi * 32768 + s * 2048, af[pi][1][s][0], af[pi][1][s][1], af[pi][1][s][2], af[pi][1][s][3]);
                        }
                    }
            }
            nbar_sync(NB_CMP, 256);
            mbar_wait_cluster(BAR(B_XC));
            if (tid < 64) {
                const uint32_t xq = sb + R_XQP + tid * 4;
                sts_hilo(sb + R_VC + tid * 2, VC_LO, (ldsf(xq) + ldsf(xq + 256)) + (ldsf(xq + 512) + ldsf(xq + 768)));
            }
            nbar_sync(NB_CMP, 256);
            if (tid == 0) TS(49);
            int kb; uint32_t ba = bvec_addr(sb + R_VC, VC_LO, zero, lane, kb);
            float acc[2][2][4] = {};
#pragma unroll
            for (int s = 0; s < 4; s++) {
                uint32_t b0, b1;
                ldsm2(ba + s * kb, b0, b1);
#pragma unroll
                for (int pi = 0; pi < 2; pi++)
                    if (pi == 0 || two) {
                        mma16816(acc[pi][0], af[pi][0][s][0], af[pi][0][s][1], af[pi][0][s][2], af[pi][0][s][3], b0, b1);
                        mma16816(acc[pi][1], af[pi][1][s][0], af[pi][1][s][1], af[pi][1][s][2], af[pi][1][s][3], b0, b1);
                    }
            }
            const int src = lane & ~3;
            uint32_t* dst = (uint32_t*)g_pE6 + ((10 * (b & 1) + warp) * 64 + (b >> 1)) * 32 + 8 * q4 + g8;
#pragma unroll
            for (int pi = 0; pi < 2; pi++)
                if (pi == 0 || two) {
                    const float v0 = __shfl_sync(0xffffffffu, acc[pi][0][0] + acc[pi][0][1], src), v1 = __shfl_sync(0xffffffffu, acc[pi][0][2] + acc[pi][0][3], src);
                    const float v2 = __shfl_sync(0xffffffffu, acc[pi][1][0] + acc[pi][1][1], src), v3 = __shfl_sync(0xffffffffu, acc[pi][1][2] + acc[pi][1][3], src);
                    xchg_word(dst + pi * (8 * 64 * 32), tagf(q4 == 0 ? v0 : q4 == 1 ? v1 : q4 == 2 ? v2 : v3, tag));
                }
        }
        if (b < NFFN) nbar_arrive(NB_G1, 288);
        if (tid == 0) TS(16);
        if (b >= NFFN && b < NFFN + 18) {
            const int p = b - NFFN;
            const float xres = __bfloat162float(prm.x[32 * p + lane]);
            const float hcol = xres + cta_reduce32<64>(g_pE6 + p * 512, sb + R_RED, tag, warp, lane, sb, 34);
            if (warp < HREP) xchg_word((uint32_t*)g_hbuf + warp * 576 + 32 * p + lane, tagf(hcol, tag));
            if (tid == 0) TS(21);
            const float f = cta_reduce32<NFFN>(g_pE8 + p * 1024, sb + R_RED + 1024, tag, warp, lane, sb, 37);
            if (warp == 0) {
                prm.out[32 * p + lane] = __float2bfloat16_rn(hcol + f);
                if (p == 0 && lane == 0) st_relaxed(&g_epoch, lds32(sb + R_TAG + 4));
            }
            if (tid == 0) TS(22);
        }
        if (b < NFFN) {
            uint32_t gf[3][2][3][4];
            {
                const uint32_t aa = sb + R_A + ((mi >> 1) * 8 + r8) * 96 + (mi & 1) * 16 + warp * 1536;
                uint32_t af[5][3][4];
                mbar_wait(BAR(B_W1));
#pragma unroll
                for (int k = 0; k < 5; k++) {
                    if (k < 4 || warp < 4) {
#pragma unroll
                        for (int mt = 0; mt < 3; mt++) ldsm4t(aa + k * 12288 + mt * 32, af[k][mt][0], af[k][mt][1], af[k][mt][2], af[k][mt][3]);
                    }
                }
                int kb; uint32_t ba = bvec_addr(sb + R_VH, VH_LO, zero, lane, kb);
                ba += warp * kb;
                nbar_sync(NB_VEC, 288);
                if (tid == 0) TS(17);
                float acc[2][3][4] = {};
#pragma unroll
                for (int k = 0; k < 5; k++) {
                    if (k < 4 || warp < 4) {
                        uint32_t b0, b1;
                        ldsm2(ba + k * 8 * kb, b0, b1);
#pragma unroll
                        for (int mt = 0; mt < 3; mt++) mma16816(acc[k & 1][mt], af[k][mt][0], af[k][mt][1], af[k][mt][2], af[k][mt][3], b0, b1);
                    }
                }
                if (q4 == 0) {
#pragma unroll
                    for (int mt = 0; mt < 3; mt++) {
                        stsf(sb + R_RED + 512 + (warp * 48 + mt * 16 + g8) * 4, (acc[0][mt][0] + acc[0][mt][1]) + (acc[1][mt][0] + acc[1][mt][1]));
                        stsf(sb + R_RED + 512 + (warp * 48 + mt * 16 + g8 + 8) * 4, (acc[0][mt][2] + acc[0][mt][3]) + (acc[1][mt][2] + acc[1][mt][3]));
                    }
                }
            }
            nbar_sync(NB_CMP, 256);
            if (tid >= 208) {
                const int i = tid - 208;
                float a = 0.f;
#pragma unroll
                for (int w = 0; w < 8; w++) a += ldsf(sb + R_RED + 512 + (w * 48 + i) * 4);
                sts_hilo(sb + R_VU + i * 2, VU_LO, __fdividef(a, 1.f + __expf(-a)));
            }
            mbar_wait(BAR(B_W2));
            frag576_load<3>(gf, sb + R_C, warp, lane);
            nbar_sync(NB_CMP, 256);
            if (tid == 0) TS(18);
            gemv576_finish<3>(gf, sb + R_VU, VU_LO, zero, g_pE8, b, tag, warp, lane);
            if (tid == 0) TS(19);
        }
    } else if (warp == 8) {
        if (lane == 0) {
            uint32_t t16 = START_OFF * 16 + 9 * pace16(4096);
            if (PF_AHEAD) {
                t16 += 4 * pace16(8192);
                int kw = 0, kc = 0;
#pragma unroll 1
                while (kw < 4 || kc < 8) {
                    const uint32_t tw = kw < 4 ? START_OFF * 16 + (9 + 2 * (b & 3) + (kw >> 1)) * pace16(4096) + LAG0_NS * 16 : 0xffffffffu;
                    const uint32_t tc = kc < 8 ? t16 : 0xffffffffu;
                    if (tw <= tc) {
                        pace_until(g0, tw);
                        tma3(sb + R_A + R_A_WUK + kw * 8192, &tm_wuk, 0, 128 * (b & 3) + 32 * kw, 2 * (b >> 2), BAR(B_WUK));
                        kw++;
                    } else {
                        pace_until(g0, tc);
                        tma3(sb + R_C + kc * 8192, &tm_ckv, 0, 64 * b + 8 * kc, 0, BAR(B_CKV0 + (kc >> 1)));
                        t16 += pace16(8192);
                        kc++;
                    }
                }
            } else {
#pragma unroll 1
                for (int k = 0; k < 4; k++) { pace_until(g0, t16); tma3(sb + R_A + R_A_WUK + k * 8192, &tm_wuk, 0, 128 * (b & 3) + 32 * k, 2 * (b >> 2), BAR(B_WUK)); t16 += pace16(8192); }
#pragma unroll 1
                for (int k = 0; k < 8; k++) {
                    pace_until(g0, t16);
                    tma3(sb + R_C + k * 8192, &tm_ckv, 0, 64 * b + 8 * k, 0, BAR(B_CKV0 + (k >> 1)));
                    t16 += pace16(8192);
                }
            }
#pragma unroll 1
            for (int k = 0; k < 4; k++) { pace_until(g0, t16); tma3(sb + R_V + k * 8192, &tm_wuv, 0, 256 * (b & 1) + 64 * k, b >> 1, BAR(B_WUV)); t16 += pace16(8192); }
#pragma unroll 1
            for (int k = 0; k < 5 - (b & 1); k++) { pace_until(g0, t16); tma3(sb + R_O + k * 8192, &tm_wo, 0, 64 * (b >> 1), 5 * (b & 1) + k, BAR(B_WO)); t16 += (b & 1) ? pace2_16(9216) : pace2_16(36864 / 5); }
#pragma unroll 1
            for (int k = 0; k < 9; k++) { pace_until(g0, t16); l2_prefetch(prm.w1 + (size_t)(k * 128 + b) * 4608, 4608); t16 += pace2_16(4608); }
#pragma unroll 1
            for (int k = 0; k < 9; k++) { pace_until(g0, t16); l2_prefetch(prm.w2 + (size_t)(k * 128 + b) * 4608, 4608); t16 += pace2_16(4608); }
            TS(20);
        }
    } else if (warp == 9) {
        const uint32_t tag = (epoch + 1u) & 1u;
        if (b < NFFN) {
            nbar_sync(NB_G1, 288);
            if (lane == 0) TS(50);
            const uint4* src = g_hbuf + (b & (HREP - 1)) * 144;
            uint4 v[5];
            int it = 0;
            uint32_t pend = lane < 16 ? 0x1fu : 0xfu;
            while (true) {
#pragma unroll
                for (int k = 0; k < 5; k++) if (pend & (1u << k)) v[k] = ld_relaxed4(src + 32 * k + lane);
#pragma unroll
                for (int k = 0; k < 5; k++) if ((pend & (1u << k)) && tags_ok(v[k], tag)) pend &= ~(1u << k);
                if (__all_sync(0xffffffffu, pend == 0)) break;
                if (++it > SPIN_LIMIT) __trap();
            }
            if (lane == 0) { mbar_arrive(BAR(B_HL)); TS(51); }
            const float pivot = __shfl_sync(0xffffffffu, untag(v[0].x), 0);
            float hv[5][4];
            float sum = 0.f, sq = 0.f;
#pragma unroll
            for (int k = 0; k < 5; k++) {
                if (k < 4 || lane < 16) {
                    hv[k][0] = untag(v[k].x) - pivot; hv[k][1] = untag(v[k].y) - pivot; hv[k][2] = untag(v[k].z) - pivot; hv[k][3] = untag(v[k].w) - pivot;
#pragma unroll
                    for (int e = 0; e < 4; e++) { sum += hv[k][e]; sq = fmaf(hv[k][e], hv[k][e], sq); }
                }
            }
#pragma unroll
            for (int o = 16; o; o >>= 1) { sum += __shfl_xor_sync(0xffffffffu, sum, o); sq += __shfl_xor_sync(0xffffffffu, sq, o); }
            const float mean = sum * (1.f / 576.f);
            const float rstd = rsqrtf(fmaxf(sq * (1.f / 576.f) - mean * mean, 0.f) + 1e-5f);
#pragma unroll
            for (int k = 0; k < 5; k++) {
                if (k < 4 || lane < 16) {
                    uint32_t h0, l0, h1, l1;
                    hilo2((hv[k][0] - mean) * rstd, (hv[k][1] - mean) * rstd, h0, l0);
                    hilo2((hv[k][2] - mean) * rstd, (hv[k][3] - mean) * rstd, h1, l1);
                    sts64(sb + R_VH + (32 * k + lane) * 8, h0, h1);
                    sts64(sb + R_VH + VH_LO + (32 * k + lane) * 8, l0, l1);
                }
            }
            nbar_arrive(NB_VEC, 288);
        }
    } else {
        if (warp == 11) {
            nbar_sync(NB_G3, 288);
            if (lane == 0) {
                asm volatile("cp.async.bulk.tensor.4d.global.shared::cta.tile.bulk_group [%0, {%1, %2, %3, %4}], [%5];"
                             ::"l"(&tm_st), "r"(0), "r"(b >> 1), "r"(b & 1), "r"(0), "r"(sb + R_STST) : "memory");
                asm volatile("cp.async.bulk.tensor.4d.global.shared::cta.tile.bulk_group [%0, {%1, %2, %3, %4}], [%5];"
                             ::"l"(&tm_op), "r"(0), "r"(b >> 1), "r"(b & 1), "r"(0), "r"(sb + R_INBOX) : "memory");
                asm volatile("cp.async.bulk.commit_group;" ::: "memory");
                asm volatile("cp.async.bulk.wait_group.read 0;" ::: "memory");
                TS(33);
            }
            __syncwarp();
            const uint32_t fv = epoch + 1u;
            if (!E4_LL && lane < FREP) red_max((unsigned*)(g_flagB + (lane * 128 + b) * 2), fv);
            if (lane == 0) {
                TS(60);
                if (b < NFFN) {
                    mbar_wait(BAR(B_FREEC));
                    mbar_wait(BAR(B_E4));
                    unsigned g1 = gtime();
                    uint32_t t16 = 0;
#pragma unroll 1
                    for (int k = 0; k < 12; k++) {
                        if (k == 6 && JIT2_GATE) { mbar_wait(BAR(B_HL)); g1 = gtime(); t16 = 0; }
                        pace_until(g1, t16);
                        if (k >= 6) tma3(sb + R_C + (k - 6) * 9216, &tm_w2, 0, 48 * b + 8 * (k - 6), 0, BAR(B_W2));
                        else tma2(sb + R_A + k * 9216, &tm_w1, 48 * b, 96 * k, BAR(B_W1));
                        t16 += k < 6 ? jit16(9216, NFFN) : (uint32_t)((uint64_t)9216 * NFFN * 16u / JIT2_GBS);
                    }
                }
                asm volatile("cp.async.bulk.wait_group 0;" ::: "memory");
                TS(61);
            }
        }
    }
}

typedef CUresult (*EncodeTiledFn)(CUtensorMap*, CUtensorMapDataType, cuuint32_t, void*, const cuuint64_t*, const cuuint64_t*,
                                  const cuuint32_t*, const cuuint32_t*, CUtensorMapInterleave, CUtensorMapSwizzle,
                                  CUtensorMapL2promotion, CUtensorMapFloatOOBfill);

bool make_map(EncodeTiledFn fn, CUtensorMap* m, const void* base, int rank, const cuuint64_t* dims, const cuuint64_t* strides,
              const cuuint32_t* box, CUtensorMapSwizzle sw) {
    cuuint32_t es[3] = {1, 1, 1};
    return fn(m, CU_TENSOR_MAP_DATA_TYPE_BFLOAT16, rank, const_cast<void*>(base), dims, strides, box, es,
              CU_TENSOR_MAP_INTERLEAVE_NONE, sw, (CUtensorMapL2promotion)L2PROMO, CU_TENSOR_MAP_FLOAT_OOB_FILL_NONE) == CUDA_SUCCESS;
}

}

extern "C" void kernel_launch(void* const* d_in, const int* in_sizes, int n_in, void* d_out, int out_size) {
    (void)in_sizes; (void)n_in; (void)out_size;
    static EncodeTiledFn encode = nullptr;
    if (!encode) {
        void* fn = nullptr;
        cudaDriverEntryPointQueryResult qr;
        cudaGetDriverEntryPoint("cuTensorMapEncodeTiled", &fn, cudaEnableDefault, &qr);
        encode = (EncodeTiledFn)fn;
        cudaFuncSetAttribute(fused_decode_kernel, cudaFuncAttributeMaxDynamicSharedMemorySize, SMEM_BYTES);
    }
    CUtensorMap tm_op, tm_st, tm_wuk, tm_ckv, tm_wuv, tm_wo, tm_w1, tm_w2;
    {
        void* op = nullptr;
        cudaGetSymbolAddress(&op, g_opart);
        cuuint64_t d[4] = {128, 64, 2, 32}, s[3] = {512, 32768, 65536}; cuuint32_t bx[4] = {128, 1, 1, 32}, es[4] = {1, 1, 1, 1};
        encode(&tm_op, CU_TENSOR_MAP_DATA_TYPE_UINT32, 4, op, d, s, bx, es, CU_TENSOR_MAP_INTERLEAVE_NONE, CU_TENSOR_MAP_SWIZZLE_NONE,
               CU_TENSOR_MAP_L2_PROMOTION_NONE, CU_TENSOR_MAP_FLOAT_OOB_FILL_NONE);
        cudaGetSymbolAddress(&op, g_stats);
        cuuint64_t d2[4] = {8, 64, 2, 4}, s2[3] = {32, 2048, 4096}; cuuint32_t bx2[4] = {8, 1, 1, 4};
        encode(&tm_st, CU_TENSOR_MAP_DATA_TYPE_UINT32, 4, op, d2, s2, bx2, es, CU_TENSOR_MAP_INTERLEAVE_NONE, CU_TENSOR_MAP_SWIZZLE_NONE,
               CU_TENSOR_MAP_L2_PROMOTION_NONE, CU_TENSOR_MAP_FLOAT_OOB_FILL_NONE);
    }
    {
        cuuint64_t d[3] = {64, 512, 64}, s[2] = {8192, 128}; cuuint32_t bx[3] = {64, 32, 2};
        make_map(encode, &tm_wuk, d_in[3], 3, d, s, bx, CU_TENSOR_MAP_SWIZZLE_128B);
    }
    {
        cuuint64_t d[3] = {64, 8192, 8}, s[2] = {1024, 128}; cuuint32_t bx[3] = {64, CKV_CONTIG ? 8u : 64u, CKV_CONTIG ? 8u : 1u};
        make_map(encode, &tm_ckv, d_in[1], 3, d, s, bx, CU_TENSOR_MAP_SWIZZLE_128B);
    }
    {
        cuuint64_t d[3] = {64, 512, 64}, s[2] = {8192, 128}; cuuint32_t bx[3] = {64, 64, 1};
        make_map(encode, &tm_wuv, d_in[4], 3, d, s, bx, CU_TENSOR_MAP_SWIZZLE_128B);
    }
    {
        cuuint64_t d[3] = {64, 4096, 9}, s[2] = {1152, 128}; cuuint32_t bx[3] = {64, 64, 1};
        make_map(encode, &tm_wo, d_in[5], 3, d, s, bx, CU_TENSOR_MAP_SWIZZLE_128B);
    }
    {
        cuuint64_t d[2] = {4608, 576}, s[1] = {9216}; cuuint32_t bx[2] = {48, 96};
        make_map(encode, &tm_w1, d_in[7], 2, d, s, bx, CU_TENSOR_MAP_SWIZZLE_NONE);
    }
    {
        cuuint64_t d[3] = {64, 4608, 9}, s[2] = {1152, 128}; cuuint32_t bx[3] = {64, 8, 9};
        make_map(encode, &tm_w2, d_in[8], 3, d, s, bx, CU_TENSOR_MAP_SWIZZLE_128B);
    }
    Params prm;
    prm.x = (const __nv_bfloat16*)d_in[0];
    prm.wq = (const __nv_bfloat16*)d_in[2];
    prm.wuk = (const char*)d_in[3];
    prm.wo = (const char*)d_in[5];
    prm.w1 = (const char*)d_in[7];
    prm.w2 = (const char*)d_in[8];
    prm.out = (__nv_bfloat16*)d_out;
    fused_decode_kernel<<<NCTA, NTHREADS, SMEM_BYTES, cudaStreamPerThread>>>(tm_op, tm_st, tm_wuk, tm_ckv, tm_wuv, tm_wo, tm_w1, tm_w2, prm);
}
```

```cpp
#include <cuda_runtime.h>
#include <cuda_bf16.h>
#include <cuda.h>
#include <stdint.h>

namespace {

constexpr int NCTA = 128;
constexpr int NFFN = 96;
constexpr int NTHREADS = 384;
constexpr int SPIN_LIMIT = 1 << 22;

constexpr uint32_t R_A = 0;
constexpr uint32_t R_A_WUK = 36864;
constexpr uint32_t R_C = 71680;
constexpr uint32_t R_V = R_C + 65536;
constexpr uint32_t R_O = R_V + 32768;
constexpr uint32_t R_P = R_O + 40960;
constexpr uint32_t R_RED = R_P + 4096;
constexpr uint32_t R_VXN = R_RED + 4096;
constexpr uint32_t VXN_LO = 576 + 16;
constexpr uint32_t R_XQP = R_VXN + 1280;
constexpr uint32_t R_VQ = R_XQP + 1024;
constexpr uint32_t VQ_LO = 256 + 16;
constexpr uint32_t R_VO = R_VQ + 640;
constexpr uint32_t VO_LO = 512 + 16;
constexpr uint32_t R_VC = R_VO + 1088;
constexpr uint32_t VC_LO = 128 + 16;
constexpr uint32_t R_VH = R_VC + 320;
constexpr uint32_t VH_LO = 1152 + 16;
constexpr uint32_t R_VU = R_VH + 2432;
constexpr uint32_t VU_LO = 96 + 16;
constexpr uint32_t R_ZERO = R_VU + 256 + 64;
constexpr uint32_t R_WTS = R_VU + 384;
constexpr uint32_t R_SMAX = R_WTS + 1024;
constexpr uint32_t R_SSUM = R_SMAX + 512;
constexpr uint32_t R_ST = R_SSUM + 512;
constexpr uint32_t R_TAG = R_ST + 512;
constexpr uint32_t R_BAR = R_TAG + 64;
constexpr uint32_t R_TS = R_BAR + 24 * 8;
constexpr uint32_t SMEM_USED = R_TS + 64 * 8;
constexpr uint32_t SMEM_BYTES = SMEM_USED + 1024;
static_assert(SMEM_BYTES <= 232448, "smem");
static_assert(R_P % 1024 == 0 && R_C % 1024 == 0 && R_V % 1024 == 0 && R_O % 1024 == 0, "align");

enum { B_WQ = 0, B_WUK, B_CKV0, B_CKV1, B_CKV2, B_CKV3, B_WUV, B_WO, B_W1, B_W2, B_FS, B_FREEC, B_XQ, B_QA, B_E4, B_FREEA, B_ST, B_IN, B_XC, B_SL, B_HL, B_RST, B_DD, NBAR };
constexpr uint32_t R_INBOX = R_A + 55296;
constexpr uint32_t R_STST = R_XQP;
static_assert(R_XQP % 128 == 0 && R_INBOX % 128 == 0, "align");
enum { NB_VEC = 1, NB_CMP = 2, NB_WG0 = 3, NB_G1 = 4, NB_G2 = 5, NB_G3 = 6, NB_INIT = 7 };

#define RATE_GBS 3050
#define CKV_CONTIG 0
#define DELAY_E2 650
#define DELAY_E4 300
#define POLL_SLEEP 0
#define L2PROMO 0
#define JIT_GBS 2500
#define RATE2_GBS RATE_GBS
#define POLICY 0
#define EARLY_FLAG 2
#define JIT_AFTER_E4 1
#define PROBE 0
#define BUSY_FROM B_FS
#define LAG_NS 1200
#define JIT2_GBS 3500
#define JIT2_GATE 0
#define PF_AHEAD 0
#define LAG0_NS 700
#define E4_LL 0
#define E2_LDG 0
#define PACE_SLEEP 20
#define EXP_NOJIT 0
#define QABS_XCHG 2
#define JIT2_DELAY 900
#define G_EARLY 0
#define FLAG_DELAY 0
#define W1_TMA_BOXES 6
#define JIT_PAUSE_AT 99
#define W2_START 0
#define START_OFF 0
__host__ __device__ constexpr uint32_t pace16(uint32_t bytes, uint32_t nctas = 128) { return (uint32_t)((uint64_t)bytes * nctas * 16u / RATE_GBS); }
__host__ __device__ constexpr uint32_t pace2_16(uint32_t bytes, uint32_t nctas = 128) { return (uint32_t)((uint64_t)bytes * nctas * 16u / RATE2_GBS); }
__host__ __device__ constexpr uint32_t jit16(uint32_t bytes, uint32_t nctas) { return (uint32_t)((uint64_t)bytes * nctas * 16u / JIT_GBS); }
constexpr uint32_t CKV_GS = CKV_CONTIG ? 8192 : 1024;
constexpr uint32_t CKV_BS = CKV_CONTIG ? 1024 : 8192;

constexpr int HREP = 4;

__device__ unsigned g_epoch;
constexpr int FREP = 4;
__device__ __align__(128) uint4 g_flagB[FREP * 128 * 2];
__device__ __align__(128) uint4 g_xq[128 * 8];
__device__ __align__(1024) uint4 g_qabs[2048];
__device__ __align__(1024) uint4 g_opart[64 * 64 * 32];
__device__ __align__(1024) uint4 g_stats[8 * 64 * 2];
__device__ __align__(128) uint4 g_pE6[18 * 64 * 8];
__device__ __align__(128) uint4 g_hbuf[HREP * 144];
__device__ __align__(128) uint4 g_pE8[18 * 128 * 8];

#define TS(k) do { } while (0)

struct Params {
    const __nv_bfloat16* x;
    const __nv_bfloat16* wq;
    const char* wuk;
    const char* wo;
    const char* w1;
    const char* w2;
    __nv_bfloat16* out;
};

__device__ __forceinline__ uint32_t smem_u32(const void* p) { return (uint32_t)__cvta_generic_to_shared(p); }
__device__ __forceinline__ void mbar_init(uint32_t bar, uint32_t cnt) {
    asm volatile("mbarrier.init.shared::cta.b64 [%0], %1;" ::"r"(bar), "r"(cnt) : "memory");
}
__device__ __forceinline__ void mbar_expect_tx(uint32_t bar, uint32_t bytes) {
    asm volatile("mbarrier.arrive.expect_tx.shared::cta.b64 _, [%0], %1;" ::"r"(bar), "r"(bytes) : "memory");
}
__device__ __forceinline__ void mbar_arrive(uint32_t bar) {
    asm volatile("mbarrier.arrive.shared::cta.b64 _, [%0];" ::"r"(bar) : "memory");
}
__device__ __forceinline__ bool mbar_try(uint32_t bar, uint32_t parity) {
    uint32_t ok;
    asm volatile("{\n.reg .pred p;\nmbarrier.try_wait.parity.shared::cta.b64 p, [%1], %2;\nselp.u32 %0, 1, 0, p;\n}"
                 : "=r"(ok) : "r"(bar), "r"(parity) : "memory");
    return ok;
}
__device__ __forceinline__ bool mbar_test(uint32_t bar) {
    uint32_t ok;
    asm volatile("{\n.reg .pred p;\nmbarrier.test_wait.parity.shared::cta.b64 p, [%1], 0;\nselp.u32 %0, 1, 0, p;\n}" : "=r"(ok) : "r"(bar) : "memory");
    return ok;
}
__device__ __forceinline__ void mbar_wait(uint32_t bar) {
    int it = 0;
    while (!mbar_try(bar, 0)) { if (++it > SPIN_LIMIT) __trap(); }
}
__device__ __forceinline__ void mbar_wait_cluster(uint32_t bar) {
    int it = 0;
    while (true) {
        uint32_t ok;
        asm volatile("{\n.reg .pred p;\nmbarrier.try_wait.parity.acquire.cluster.shared::cta.b64 p, [%1], 0;\nselp.u32 %0, 1, 0, p;\n}" : "=r"(ok) : "r"(bar) : "memory");
        if (ok) break;
        if (++it > SPIN_LIMIT) __trap();
    }
}
__device__ __forceinline__ uint32_t mapa(uint32_t a, uint32_t rank) { uint32_t d; asm volatile("mapa.shared::cluster.u32 %0, %1, %2;" : "=r"(d) : "r"(a), "r"(rank)); return d; }
__device__ __forceinline__ void st_async_f32(uint32_t a, float v, uint32_t bar) {
    asm volatile("st.async.weak.shared::cluster.mbarrier::complete_tx::bytes.f32 [%0], %1, [%2];" ::"r"(a), "f"(v), "r"(bar) : "memory");
}
__device__ __forceinline__ void st_async_v4(uint32_t a, uint32_t x, uint32_t y, uint32_t z, uint32_t w, uint32_t bar) {
    asm volatile("st.async.weak.shared::cluster.mbarrier::complete_tx::bytes.v4.b32 [%0], {%1,%2,%3,%4}, [%5];" ::"r"(a), "r"(x), "r"(y), "r"(z), "r"(w), "r"(bar) : "memory");
}
__device__ __forceinline__ void nbar_sync(int id, int n) { asm volatile("bar.sync %0, %1;" ::"r"(id), "r"(n) : "memory"); }
__device__ __forceinline__ void nbar_arrive(int id, int n) { asm volatile("bar.arrive %0, %1;" ::"r"(id), "r"(n) : "memory"); }
__device__ __forceinline__ void fence_async_smem() { asm volatile("fence.proxy.async.shared::cta;" ::: "memory"); }

__device__ __forceinline__ void cp_async16(uint32_t dst, const void* src) {
    asm volatile("cp.async.cg.shared.global [%0], [%1], 16;" ::"r"(dst), "l"(src) : "memory");
}
__device__ __forceinline__ void cp_async_arrive(uint32_t bar) {
    asm volatile("cp.async.mbarrier.arrive.noinc.shared::cta.b64 [%0];" ::"r"(bar) : "memory");
}
__device__ __forceinline__ void tma3(uint32_t dst, const CUtensorMap* tm, int c0, int c1, int c2, uint32_t bar) {
    asm volatile("cp.async.bulk.tensor.3d.shared::cluster.global.tile.mbarrier::complete_tx::bytes [%0], [%1, {%2, %3, %4}], [%5];"
                 ::"r"(dst), "l"(tm), "r"(c0), "r"(c1), "r"(c2), "r"(bar) : "memory");
}
__device__ __forceinline__ void tma2(uint32_t dst, const CUtensorMap* tm, int c0, int c1, uint32_t bar) {
    asm volatile("cp.async.bulk.tensor.2d.shared::cluster.global.tile.mbarrier::complete_tx::bytes [%0], [%1, {%2, %3}], [%4];"
                 ::"r"(dst), "l"(tm), "r"(c0), "r"(c1), "r"(bar) : "memory");
}
__device__ __forceinline__ void l2_prefetch(const void* p, uint32_t bytes) {
    asm volatile("cp.async.bulk.prefetch.L2.global [%0], %1;" ::"l"(p), "r"(bytes) : "memory");
}
__device__ __forceinline__ void prefetch_tmap(const CUtensorMap* tm) {
    asm volatile("prefetch.tensormap [%0];" ::"l"(tm) : "memory");
}
__device__ __forceinline__ void ldsm4(uint32_t a, uint32_t& r0, uint32_t& r1, uint32_t& r2, uint32_t& r3) {
    asm volatile("ldmatrix.sync.aligned.m8n8.x4.shared.b16 {%0,%1,%2,%3}, [%4];" : "=r"(r0), "=r"(r1), "=r"(r2), "=r"(r3) : "r"(a) : "memory");
}
__device__ __forceinline__ void ldsm4t(uint32_t a, uint32_t& r0, uint32_t& r1, uint32_t& r2, uint32_t& r3) {
    asm volatile("ldmatrix.sync.aligned.m8n8.x4.trans.shared.b16 {%0,%1,%2,%3}, [%4];" : "=r"(r0), "=r"(r1), "=r"(r2), "=r"(r3) : "r"(a) : "memory");
}
__device__ __forceinline__ void ldsm2(uint32_t a, uint32_t& r0, uint32_t& r1) {
    asm volatile("ldmatrix.sync.aligned.m8n8.x2.shared.b16 {%0,%1}, [%2];" : "=r"(r0), "=r"(r1) : "r"(a) : "memory");
}
__device__ __forceinline__ void stsm4t(uint32_t a, uint32_t r0, uint32_t r1, uint32_t r2, uint32_t r3) {
    asm volatile("stmatrix.sync.aligned.m8n8.x4.trans.shared.b16 [%0], {%1,%2,%3,%4};" ::"r"(a), "r"(r0), "r"(r1), "r"(r2), "r"(r3) : "memory");
}
__device__ __forceinline__ void mma16816(float* d, uint32_t a0, uint32_t a1, uint32_t a2, uint32_t a3, uint32_t b0, uint32_t b1) {
    asm volatile("mma.sync.aligned.m16n8k16.row.col.f32.bf16.bf16.f32 {%0,%1,%2,%3}, {%4,%5,%6,%7}, {%8,%9}, {%0,%1,%2,%3};"
                 : "+f"(d[0]), "+f"(d[1]), "+f"(d[2]), "+f"(d[3]) : "r"(a0), "r"(a1), "r"(a2), "r"(a3), "r"(b0), "r"(b1));
}
__device__ __forceinline__ uint4 ld_relaxed4(const void* p) {
    uint4 v;
    asm volatile("ld.relaxed.gpu.global.v4.u32 {%0,%1,%2,%3}, [%4];" : "=r"(v.x), "=r"(v.y), "=r"(v.z), "=r"(v.w) : "l"(p) : "memory");
    return v;
}
__device__ __forceinline__ uint2 ld_relaxed2(const void* p) {
    uint2 v;
    asm volatile("ld.relaxed.gpu.global.v2.u32 {%0,%1}, [%2];" : "=r"(v.x), "=r"(v.y) : "l"(p) : "memory");
    return v;
}
__device__ __forceinline__ uint32_t ld_relaxed(const void* p) {
    uint32_t v;
    asm volatile("ld.relaxed.gpu.global.u32 %0, [%1];" : "=r"(v) : "l"(p) : "memory");
    return v;
}
__device__ __forceinline__ void st_relaxed4(void* p, uint32_t a, uint32_t b, uint32_t c, uint32_t d) {
    asm volatile("st.relaxed.gpu.global.v4.u32 [%0], {%1,%2,%3,%4};" ::"l"(p), "r"(a), "r"(b), "r"(c), "r"(d) : "memory");
}
__device__ __forceinline__ void st_relaxed2(void* p, uint32_t a, uint32_t b) {
    asm volatile("st.relaxed.gpu.global.v2.u32 [%0], {%1,%2};" ::"l"(p), "r"(a), "r"(b) : "memory");
}
__device__ __forceinline__ void st_relaxed(void* p, uint32_t a) {
    asm volatile("st.relaxed.gpu.global.u32 [%0], %1;" ::"l"(p), "r"(a) : "memory");
}
__device__ __forceinline__ void red_add(unsigned* p, unsigned v) {
    asm volatile("red.relaxed.gpu.global.add.u32 [%0], %1;" ::"l"(p), "r"(v) : "memory");
}
#define XCHG 1
__device__ __forceinline__ void xchg_word(uint32_t* p, uint32_t v) {
    uint32_t old;
    asm volatile("atom.relaxed.gpu.global.exch.b32 %0, [%1], %2;" : "=r"(old) : "l"(p), "r"(v) : "memory");
}
__device__ __forceinline__ void red_max(unsigned* p, unsigned v) {
    asm volatile("red.relaxed.gpu.global.max.u32 [%0], %1;" ::"l"(p), "r"(v) : "memory");
}
__device__ __forceinline__ void sts32(uint32_t a, uint32_t v) { asm volatile("st.shared.u32 [%0], %1;" ::"r"(a), "r"(v) : "memory"); }
__device__ __forceinline__ void sts16(uint32_t a, uint16_t v) { asm volatile("st.shared.u16 [%0], %1;" ::"r"(a), "h"(v) : "memory"); }
__device__ __forceinline__ void stsf(uint32_t a, float v) { asm volatile("st.shared.f32 [%0], %1;" ::"r"(a), "f"(v) : "memory"); }
__device__ __forceinline__ void sts128(uint32_t a, uint32_t x, uint32_t y, uint32_t z, uint32_t w) {
    asm volatile("st.shared.v4.u32 [%0], {%1,%2,%3,%4};" ::"r"(a), "r"(x), "r"(y), "r"(z), "r"(w) : "memory");
}
__device__ __forceinline__ uint4 lds128(uint32_t a) {
    uint4 v; asm volatile("ld.shared.v4.u32 {%0,%1,%2,%3}, [%4];" : "=r"(v.x), "=r"(v.y), "=r"(v.z), "=r"(v.w) : "r"(a) : "memory"); return v;
}
__device__ __forceinline__ uint32_t add_bf16x2(uint32_t a, uint32_t b) { uint32_t r; asm("add.rn.bf16x2 %0, %1, %2;" : "=r"(r) : "r"(a), "r"(b)); return r; }
__device__ __forceinline__ float ldsf(uint32_t a) { float v; asm volatile("ld.shared.f32 %0, [%1];" : "=f"(v) : "r"(a) : "memory"); return v; }
__device__ __forceinline__ uint32_t lds32(uint32_t a) { uint32_t v; asm volatile("ld.shared.u32 %0, [%1];" : "=r"(v) : "r"(a) : "memory"); return v; }
__device__ __forceinline__ float2 ldsf2(uint32_t a) { float2 v; asm volatile("ld.shared.v2.f32 {%0,%1}, [%2];" : "=f"(v.x), "=f"(v.y) : "r"(a) : "memory"); return v; }
__device__ __forceinline__ unsigned gtime() { unsigned t; asm volatile("mov.u32 %0, %%globaltimer_lo;" : "=r"(t)::"memory"); return t; }
__device__ __forceinline__ float ex2(float x) { float y; asm("ex2.approx.ftz.f32 %0, %1;" : "=f"(y) : "f"(x)); return y; }

__device__ __forceinline__ uint32_t tagf(float v, uint32_t tag) { return (__float_as_uint(v) & ~3u) | 2u | tag; }
__device__ __forceinline__ float untag(uint32_t w) { return __uint_as_float(w & ~3u); }
__device__ __forceinline__ bool tags_ok(const uint4& v, uint32_t tag) {
    const uint32_t t = tag | 2u;
    return (((v.x ^ t) | (v.y ^ t) | (v.z ^ t) | (v.w ^ t)) & 3u) == 0;
}
__device__ __forceinline__ bool tags1_ok(const uint4& v, uint32_t tag) { return (((v.x ^ tag) | (v.y ^ tag) | (v.z ^ tag) | (v.w ^ tag)) & 1u) == 0; }
__device__ __forceinline__ int wait_flags16(const uint4* flags, uint32_t val, int lane) {
    bool ok = lane >= 16;
    const uint32_t* f = (const uint32_t*)(flags + 2 * (lane & 15));
    int it = 0;
    while (true) {
        if (!ok) ok = ld_relaxed(f) == val;
        if (__all_sync(0xffffffffu, ok)) break;
        if (++it > SPIN_LIMIT) __trap();
    }
    return it;
}
__device__ __forceinline__ void poll8(uint4* v, const uint4* p, int stride, uint32_t tag) {
    uint32_t pend = 0xffu;
    int it = 0;
    while (true) {
#pragma unroll
        for (int i = 0; i < 8; i++) if (pend & (1u << i)) v[i] = ld_relaxed4(p + i * stride);
#pragma unroll
        for (int i = 0; i < 8; i++) if (tags1_ok(v[i], tag)) pend &= ~(1u << i);
        if (pend == 0) break;
        if (++it > SPIN_LIMIT) __trap();
    }
}
__device__ __forceinline__ void delay_ns(unsigned ns) { if (ns) { const unsigned t0 = gtime(); while (gtime() - t0 < ns) { } } }
__device__ __forceinline__ uint32_t pack_tagged(float lo, float hi, uint32_t tag) {
    uint32_t r0 = __float_as_uint(lo) + 0x10000u;
    uint32_t r1 = __float_as_uint(hi) + 0x8000u;
    return (__byte_perm(r0, r1, 0x7632) & ~1u) | tag;
}
__device__ __forceinline__ uint32_t pack_bf16(float lo, float hi) {
    uint32_t r;
    asm("cvt.rn.bf16x2.f32 %0, %1, %2;" : "=r"(r) : "f"(hi), "f"(lo));
    return r;
}
__device__ __forceinline__ void pace_until(unsigned g0, uint32_t t16) {
    const unsigned t = t16 >> 4;
    while (gtime() - g0 < t) {
        __nanosleep(PACE_SLEEP);
    }
}
__device__ __forceinline__ void sts64(uint32_t a, uint32_t x, uint32_t y) { asm volatile("st.shared.v2.u32 [%0], {%1,%2};" ::"r"(a), "r"(x), "r"(y) : "memory"); }
__device__ __forceinline__ void hilo2(float v0, float v1, uint32_t& hi, uint32_t& lo) {
    asm("cvt.rn.bf16x2.f32 %0, %1, %2;" : "=r"(hi) : "f"(v1), "f"(v0));
    float r0 = v0 - __uint_as_float(hi << 16), r1 = v1 - __uint_as_float(hi & 0xffff0000u);
    asm("cvt.rn.bf16x2.f32 %0, %1, %2;" : "=r"(lo) : "f"(r1), "f"(r0));
}
__device__ __forceinline__ void sts_hilo(uint32_t a_hi, uint32_t lo_off, float v) {
    __nv_bfloat16 h = __float2bfloat16_rn(v);
    __nv_bfloat16 l = __float2bfloat16_rn(v - __bfloat162float(h));
    sts16(a_hi, __bfloat16_as_ushort(h));
    sts16(a_hi + lo_off, __bfloat16_as_ushort(l));
}
__device__ __forceinline__ float bf16lo(uint32_t w) { return __uint_as_float(w << 16); }
__device__ __forceinline__ float bf16hi(uint32_t w) { return __uint_as_float(w & 0xffff0000u); }
__device__ __forceinline__ float warp_sum(float v) {
#pragma unroll
    for (int o = 16; o; o >>= 1) v += __shfl_xor_sync(0xffffffffu, v, o);
    return v;
}
__device__ __forceinline__ float warp_max(float v) {
#pragma unroll
    for (int o = 16; o; o >>= 1) v = fmaxf(v, __shfl_xor_sync(0xffffffffu, v, o));
    return v;
}

__device__ __forceinline__ uint64_t make_desc(uint32_t addr, uint32_t lbo, uint32_t sbo) {
    return (uint64_t)((addr & 0x3FFFF) >> 4) | ((uint64_t)(lbo >> 4) << 16) | ((uint64_t)(sbo >> 4) << 32) | (1ull << 62);
}
__device__ __forceinline__ uint64_t desc_add(uint64_t d, uint32_t off) { return d + (uint64_t)(off >> 4); }
__device__ __forceinline__ void wg_fence() { asm volatile("wgmma.fence.sync.aligned;" ::: "memory"); }
__device__ __forceinline__ void wg_commit() { asm volatile("wgmma.commit_group.sync.aligned;" ::: "memory"); }
__device__ __forceinline__ void wg_wait0() { asm volatile("wgmma.wait_group.sync.aligned 0;" ::: "memory"); }
template <int TA>
__device__ __forceinline__ void wgmma_n32(float* d, uint64_t da, uint64_t db, int scale_d) {
    asm volatile("{\n.reg .pred p;\nsetp.ne.b32 p, %18, 0;\n"
                 "wgmma.mma_async.sync.aligned.m64n32k16.f32.bf16.bf16 "
                 "{%0,%1,%2,%3,%4,%5,%6,%7,%8,%9,%10,%11,%12,%13,%14,%15}, %16, %17, p, 1, 1, %19, 0;\n}"
                 : "+f"(d[0]), "+f"(d[1]), "+f"(d[2]), "+f"(d[3]), "+f"(d[4]), "+f"(d[5]), "+f"(d[6]), "+f"(d[7]),
                   "+f"(d[8]), "+f"(d[9]), "+f"(d[10]), "+f"(d[11]), "+f"(d[12]), "+f"(d[13]), "+f"(d[14]), "+f"(d[15])
                 : "l"(da), "l"(db), "r"(scale_d), "n"(TA));
}

__device__ __forceinline__ uint32_t bvec_addr(uint32_t base, uint32_t lo_off, uint32_t zero, int lane, int& kstep_bytes) {
    int n = lane & 7, kh = (lane >> 3) & 1;
    if (n < 2) { kstep_bytes = 32; return base + n * lo_off + kh * 16; }
    kstep_bytes = 0;
    return zero;
}

template <int NP>
__device__ __forceinline__ float cta_reduce32(const uint4* part, uint32_t red, uint32_t tag, int warp, int lane, uint32_t sb = 0, int dbg = 0) {
    constexpr int NI = NP / 32;
    const uint4* src = part + (warp * (NP / 8) + (lane >> 3)) * 8 + (lane & 7);
    uint4 v[NI];
    uint32_t pend = (1u << NI) - 1u;
    int it = 0;
    while (true) {
#pragma unroll
        for (int k = 0; k < NI; k++) if (pend & (1u << k)) v[k] = ld_relaxed4(src + k * 32);
#pragma unroll
        for (int k = 0; k < NI; k++) if (tags_ok(v[k], tag)) pend &= ~(1u << k);
        if (__all_sync(0xffffffffu, pend == 0)) break;
        if (++it > SPIN_LIMIT) __trap();
    }
    float x0 = 0.f, x1 = 0.f, x2 = 0.f, x3 = 0.f;
#pragma unroll
    for (int k = 0; k < NI; k++) { x0 += untag(v[k].x); x1 += untag(v[k].y); x2 += untag(v[k].z); x3 += untag(v[k].w); }
    const bool b4 = lane & 16, b3 = lane & 8;
    const float t0 = (b4 ? x2 : x0) + __shfl_xor_sync(0xffffffffu, b4 ? x0 : x2, 16);
    const float t1 = (b4 ? x3 : x1) + __shfl_xor_sync(0xffffffffu, b4 ? x1 : x3, 16);
    const float s0 = (b3 ? t1 : t0) + __shfl_xor_sync(0xffffffffu, b3 ? t0 : t1, 8);
    stsf(red + (warp * 32 + 4 * (lane & 7) + 2 * (lane >> 4) + ((lane >> 3) & 1)) * 4, s0);
    nbar_sync(NB_CMP, 256);
    float t = 0.f;
#pragma unroll
    for (int w = 0; w < 8; w++) t += ldsf(red + (w * 32 + lane) * 4);
    return t;
}

template <int KSTEPS>
__device__ __forceinline__ void frag576_load(uint32_t (*af)[2][KSTEPS][4], uint32_t tile, int warp, int lane) {
    const int mi = lane >> 3, r8 = lane & 7;
    const uint32_t base = tile + (mi >> 1) * 9216 + (warp >> 1) * 1024 + r8 * 128;
    const int cc = (warp & 1) * 4 + (mi & 1);
    const uint32_t a0 = base + ((cc ^ r8) << 4), a1 = base + (((cc + 2) ^ r8) << 4);
#pragma unroll
    for (int pi = 0; pi < 3; pi++) {
        if (pi < 2 || warp < 2) {
#pragma unroll
            for (int s = 0; s < KSTEPS; s++) {
                ldsm4t(a0 + pi * 4096 + s * 18432, af[pi][0][s][0], af[pi][0][s][1], af[pi][0][s][2], af[pi][0][s][3]);
                ldsm4t(a1 + pi * 4096 + s * 18432, af[pi][1][s][0], af[pi][1][s][1], af[pi][1][s][2], af[pi][1][s][3]);
            }
        }
    }
}
template <int KSTEPS>
__device__ __forceinline__ void gemv576_finish(uint32_t (*af)[2][KSTEPS][4], uint32_t vec, uint32_t lo_off, uint32_t zero, uint4* part, int b,
                                               uint32_t tag, int warp, int lane) {
    int kb; uint32_t ba = bvec_addr(vec, lo_off, zero, lane, kb);
    uint32_t bf[KSTEPS][2];
#pragma unroll
    for (int s = 0; s < KSTEPS; s++) ldsm2(ba + s * kb, bf[s][0], bf[s][1]);
    float acc[3][2][4] = {};
#pragma unroll
    for (int s = 0; s < KSTEPS; s++)
#pragma unroll
        for (int pi = 0; pi < 3; pi++)
            if (pi < 2 || warp < 2) {
#pragma unroll
                for (int tl = 0; tl < 2; tl++)
                    mma16816(acc[pi][tl], af[pi][tl][s][0], af[pi][tl][s][1], af[pi][tl][s][2], af[pi][tl][s][3], bf[s][0], bf[s][1]);
            }
    const int src = lane & ~3, q = lane & 3;
    uint32_t* dst = (uint32_t*)part + (warp * 128 + b) * 32 + 8 * q + (lane >> 2);
#pragma unroll
    for (int pi = 0; pi < 3; pi++)
        if (pi < 2 || warp < 2) {
            const float v0 = __shfl_sync(0xffffffffu, acc[pi][0][0] + acc[pi][0][1], src), v1 = __shfl_sync(0xffffffffu, acc[pi][0][2] + acc[pi][0][3], src);
            const float v2 = __shfl_sync(0xffffffffu, acc[pi][1][0] + acc[pi][1][1], src), v3 = __shfl_sync(0xffffffffu, acc[pi][1][2] + acc[pi][1][3], src);
            xchg_word(dst + pi * (8 * 128 * 32), tagf(q == 0 ? v0 : q == 1 ? v1 : q == 2 ? v2 : v3, tag));
        }
}

__global__ void __cluster_dims__(2, 1, 1) __launch_bounds__(NTHREADS, 1)
fused_decode_kernel(const __grid_constant__ CUtensorMap tm_op, const __grid_constant__ CUtensorMap tm_st, const __grid_constant__ CUtensorMap tm_wuk, const __grid_constant__ CUtensorMap tm_ckv, const __grid_constant__ CUtensorMap tm_wuv,
                    const __grid_constant__ CUtensorMap tm_wo, const __grid_constant__ CUtensorMap tm_w1,
                    const __grid_constant__ CUtensorMap tm_w2, const Params prm)
{
    extern __shared__ uint8_t smem_raw[];
    const uint32_t sb = (smem_u32(smem_raw) + 1023u) & ~1023u;
    const int tid = threadIdx.x, warp = tid >> 5, lane = tid & 31;
    const int b = blockIdx.x;
    const uint32_t bars = sb + R_BAR;
    const uint32_t zero = sb + R_ZERO;
    auto BAR = [&](int i) { return bars + 8u * i; };

    const unsigned g0 = gtime();
    if (tid == 0) TS(0);
    uint32_t xw[9];
    unsigned epoch = 0;
    auto init_barriers = [&]() {
        if (lane == 0) {
#pragma unroll
            for (int j = 0; j < 2; j++) {
                const int i = warp + 12 * j;
                if (i < NBAR) {
                    const uint32_t cnt = i == B_WQ ? 256u : ((POLICY == 3 || POLICY == 5) && i == B_W1) ? 32u : (POLICY == 0 && i == B_W1 && W1_TMA_BOXES < 6) ? (W1_TMA_BOXES ? 33u : 32u) : ((i == B_FREEC || i == B_E4 || i == B_FS || i == B_DD) ? 8u : (i == B_FREEA ? 4u : 1u));
                    mbar_init(BAR(i), cnt);
                    const uint32_t tx = i == B_WUK ? 32768u : (i >= B_CKV0 && i <= B_CKV3) ? 16384u : i == B_WUV ? 32768u
                                      : i == B_WO ? ((b & 1) ? 32768u : 40960u) : i == B_W1 ? ((POLICY == 3 || POLICY == 5) ? 0u : 9216u * W1_TMA_BOXES) : i == B_W2 ? 55296u
                                      : (i == B_XQ || i == B_XC) ? 512u : i == B_QA ? 32768u : (i == B_ST || i == B_SL) ? 128u : i == B_IN ? 16384u : 0u;
                    if (tx) mbar_expect_tx(BAR(i), tx);
                }
            }
            asm volatile("fence.mbarrier_init.release.cluster;" ::: "memory");
        }
    };
    const __nv_bfloat16* wq_src = prm.wq + (size_t)(32 * (b & 1) + (tid >> 3)) * 4096 + (b >> 1) * 64 + (tid & 7) * 8;
    const uint32_t wq_off = (tid >> 3) * 128 + (((tid & 7) ^ ((tid >> 3) & 7)) << 4);
    if (warp < 8) {
        if (!PF_AHEAD) cp_async16(sb + R_A + wq_off, wq_src);
        init_barriers();
        if (tid < 144) {
            if (b < NFFN) st_relaxed4(g_pE8 + ((tid >> 3) * 128 + b) * 8 + (tid & 7), 0, 0, 0, 0);
            if (tid < ((b & 1) ? 64 : 80)) st_relaxed4(g_pE6 + (((tid >> 3) + 10 * (b & 1)) * 64 + (b >> 1)) * 8 + (tid & 7), 0, 0, 0, 0);
        }
        else if (!E4_LL && tid >= 160 && tid < 160 + 2 * FREP) st_relaxed4(g_flagB + (((tid - 160) >> 1) * 128 + b) * 2 + (tid & 1), 0, 0, 0, 0);
        else if (tid >= 184 && tid < 192) st_relaxed4(g_xq + b * 8 + (tid - 184), 0, 0, 0, 0);
#pragma unroll 1
        for (int i = PF_AHEAD ? 0 : 1; i < 9; i++) {
            pace_until(g0, START_OFF * 16 + i * pace16(4096) + (PF_AHEAD ? LAG0_NS * 16 : 0));
            cp_async16(sb + R_A + i * 4096 + wq_off, wq_src + (size_t)i * 64 * 4096);
        }
    } else if (warp == 9) {
        init_barriers();
        epoch = ld_relaxed(&g_epoch);
#pragma unroll
        for (int i = 0; i < 9; i++) xw[i] = __ldg((const uint32_t*)prm.x + lane + 32 * i);
        if (lane < 4) sts32(zero + 4 * lane, 0u);
    } else {
        init_barriers();
        if (warp == 8) {
            if (lane < 8) {
                const CUtensorMap* t = lane == 7 ? &tm_st : lane == 0 ? &tm_ckv : lane == 1 ? &tm_wuv : lane == 2 ? &tm_wo : lane == 3 ? &tm_w1 : lane == 4 ? &tm_w2 : lane == 5 ? &tm_wuk : &tm_op;
                prefetch_tmap(t);
            }
        } else {
            epoch = ld_relaxed(&g_epoch);
            if (b >= NFFN && b < NFFN + 18 && warp == 10) st_relaxed4((uint32_t*)g_hbuf + (lane >> 3) * 576 + 32 * (b - NFFN) + (lane & 7) * 4, 0, 0, 0, 0);
        }
    }
    float ln_mean = 0.f, ln_rstd = 0.f;
    if (warp == 9) {
        float sum = 0.f;
#pragma unroll
        for (int i = 0; i < 9; i++) sum += bf16lo(xw[i]) + bf16hi(xw[i]);
        ln_mean = warp_sum(sum) * (1.f / 576.f);
        float sq = 0.f;
#pragma unroll
        for (int i = 0; i < 9; i++) { float a = bf16lo(xw[i]) - ln_mean, c = bf16hi(xw[i]) - ln_mean; sq += a * a + c * c; }
        ln_rstd = rsqrtf(warp_sum(sq) * (1.f / 576.f) + 1e-5f);
#pragma unroll
        for (int i = 0; i < 9; i++) {
            const int m = 2 * (lane + 32 * i);
            const int e = 32 * (m >> 6) + (m & 31);
            if (((m >> 5) & 1) == (b & 1)) {
                uint32_t hi, lo;
                hilo2((bf16lo(xw[i]) - ln_mean) * ln_rstd, (bf16hi(xw[i]) - ln_mean) * ln_rstd, hi, lo);
                sts32(sb + R_VXN + e * 2, hi);
                sts32(sb + R_VXN + VXN_LO + e * 2, lo);
            }
        }
        if (lane == 0) { sts32(sb + R_TAG, (epoch + 1u) & 1u); sts32(sb + R_TAG + 4, epoch + 1u); }
    }
    if (warp == 10) nbar_arrive(NB_INIT, NTHREADS); else nbar_sync(NB_INIT, NTHREADS);
    asm volatile("barrier.cluster.arrive.relaxed.aligned;" ::: "memory");
    if (warp == 10 && lane == 0 && PF_AHEAD) {
#pragma unroll 1
        for (int k = 0; k < 17; k++) {
            pace_until(g0, START_OFF * 16 + k * pace16(4096));
            l2_prefetch(k < 9 ? (const char*)prm.wq + (size_t)(k * 128 + b) * 4096 : prm.wuk + (size_t)((k - 9) * 128 + b) * 4096, 4096);
        }
    }

    if (warp < 8) {
        const int mi = lane >> 3, r8 = lane & 7, q4 = lane & 3, g8 = lane >> 2;
        cp_async_arrive(BAR(B_WQ));
        const uint32_t tag = lds32(sb + R_TAG);
        if (warp == 0 && lane < 16)
            st_relaxed4((char*)g_qabs + (2 * (b & 3) + (lane >> 3)) * 4096 + (b >> 2) * 128 + (lane & 7) * 16, tag ^ 1u, 0, 0, 0);
        {
            const int mt = warp & 3, kh = warp >> 2;
            const uint32_t aa = sb + R_A + (144 * kh + (mi >> 1) * 8 + r8) * 128 + (((2 * mt + (mi & 1)) ^ r8) << 4);
            int kb; uint32_t ba = bvec_addr(sb + R_VXN + kh * 288, VXN_LO, zero, lane, kb);
            uint32_t bf[9][2];
#pragma unroll
            for (int s = 0; s < 9; s++) ldsm2(ba + s * kb, bf[s][0], bf[s][1]);
            mbar_wait(BAR(B_WQ));
            if (tid == 0) TS(1);
            float acc[3][4] = {};
#pragma unroll
            for (int s = 0; s < 9; s++) {
                uint32_t a0, a1, a2, a3;
                ldsm4t(aa + s * 2048, a0, a1, a2, a3);
                mma16816(acc[s % 3], a0, a1, a2, a3, bf[s][0], bf[s][1]);
            }
            const float v0 = (acc[0][0] + acc[0][1]) + (acc[1][0] + acc[1][1]) + (acc[2][0] + acc[2][1]);
            const float v1 = (acc[0][2] + acc[0][3]) + (acc[1][2] + acc[1][3]) + (acc[2][2] + acc[2][3]);
            asm volatile("barrier.cluster.wait.acquire.aligned;" ::: "memory");
            const uint32_t xq = sb + R_XQP + (kh * 64 + mt * 16 + g8) * 4;
            if (q4 == 0) {
                const uint32_t rq = mapa(xq + 512, (b & 1) ^ 1), rb = mapa(BAR(B_XQ), (b & 1) ^ 1);
                st_async_f32(rq, v0, rb);
                st_async_f32(rq + 32, v1, rb);
                stsf(xq, v0); stsf(xq + 32, v1);
            }
            if (tid == 0) TS(2);
        }
        {
            const int h = b >> 2;
            const int row = 16 * warp + (mi & 1) * 8 + r8;
            const uint32_t aa = sb + R_A + R_A_WUK + (row >> 5) * 8192 + (row & 31) * 128;
            uint32_t af[8][4];
            nbar_sync(NB_CMP, 256);
            mbar_wait_cluster(BAR(B_XQ));
            if (warp < 2) {
                const uint32_t xq = sb + R_XQP + tid * 4;
                const float qv = (ldsf(xq) + ldsf(xq + 256)) + (ldsf(xq + 512) + ldsf(xq + 768));
                if (warp == (b & 1)) xchg_word((uint32_t*)g_xq + b * 32 + lane, tagf(qv, tag));
                sts_hilo(sb + R_VQ + (64 * ((b >> 1) & 1) + tid) * 2, VQ_LO, qv);
            } else if (warp == 2) {
                const uint2* src = (const uint2*)(g_xq + ((b & ~3) + ((b & 2) ^ 2)) * 8) + lane;
                uint2 v; int it = 0; bool ok = false;
                while (true) {
                    if (!ok) { v = ld_relaxed2(src); ok = (((v.x ^ (tag | 2u)) | (v.y ^ (tag | 2u))) & 3u) == 0; }
                    if (__all_sync(0xffffffffu, ok)) break;
                    if (++it > SPIN_LIMIT) __trap();
                }
                uint32_t hi, lo;
                hilo2(untag(v.x), untag(v.y), hi, lo);
                const uint32_t a = sb + R_VQ + (64 * (((b >> 1) & 1) ^ 1) + 2 * lane) * 2;
                sts32(a, hi); sts32(a + VQ_LO, lo);
            }
            mbar_wait(BAR(B_WUK));
#pragma unroll
            for (int s = 0; s < 8; s++) {
                const int cc = (s & 3) * 2 + (mi >> 1);
                ldsm4(aa + (s >> 2) * 4096 + ((cc ^ r8) << 4), af[s][0], af[s][1], af[s][2], af[s][3]);
            }
            nbar_sync(NB_CMP, 256);
            if (tid == 0) TS(3);
            int kb; uint32_t ba = bvec_addr(sb + R_VQ, VQ_LO, zero, lane, kb);
            float acc[2][4] = {};
#pragma unroll
            for (int s = 0; s < 8; s++) {
                uint32_t b0, b1;
                ldsm2(ba + s * kb, b0, b1);
                mma16816(acc[s & 1], af[s][0], af[s][1], af[s][2], af[s][3], b0, b1);
            }
            const float sc = 0.08838834764831845f * 1.4426950408889634f;
            const float v0 = ((acc[0][0] + acc[0][1]) + (acc[1][0] + acc[1][1])) * sc;
            const float v1 = ((acc[0][2] + acc[0][3]) + (acc[1][2] + acc[1][3])) * sc;
            if (q4 == 0) {
                const uint32_t st = sb + R_RED + (warp >> 2) * 128 + g8 * 2;
                const int c0 = ((warp & 3) * 2) ^ (h & 7), c1 = c0 ^ 1;
                uint32_t w0 = __bfloat16_as_ushort(__float2bfloat16_rn(v0)), w1 = __bfloat16_as_ushort(__float2bfloat16_rn(v1));
                if (g8 == 0) {
                    if ((c0 & 1) == 0) w0 = (((__float_as_uint(v0) + 0x10000u) >> 16) & 0xfffeu) | tag;
                    else w1 = (((__float_as_uint(v1) + 0x10000u) >> 16) & 0xfffeu) | tag;
                }
                sts16(st + (c0 << 4), (uint16_t)w0);
                sts16(st + (c1 << 4), (uint16_t)w1);
            }
            if (QABS_XCHG == 2) fence_async_smem();
        }
        nbar_sync(NB_CMP, 256);
        const uint32_t fval = lds32(sb + R_TAG + 4);
        if (warp == 0 && lane < 16) {
            const uint4 v = lds128(sb + R_RED + lane * 16);
            char* dst = (char*)g_qabs + (2 * (b & 3) + (lane >> 3)) * 4096 + (b >> 2) * 128 + (lane & 7) * 16;
            if ((lane & 7) == 0) {
                asm volatile("cp.async.bulk.global.shared::cta.bulk_group [%0], [%1], 128;" ::"l"(dst), "r"(sb + R_RED + lane * 16) : "memory");
                asm volatile("cp.async.bulk.commit_group;" ::: "memory");
            }
        }
        if (tid == 0) {
            TS(4);
            delay_ns(DELAY_E2);
            TS(5);
            const uint32_t half = (b & 1) * 16384;
            asm volatile("cp.async.bulk.shared::cluster.global.mbarrier::complete_tx::bytes.multicast::cluster [%0], [%1], 16384, [%2], %3;"
                         ::"r"(sb + R_A + half), "l"((const char*)g_qabs + half), "r"(BAR(B_QA)), "h"((uint16_t)3) : "memory");
        }
        mbar_wait(BAR(B_QA));
        {
#pragma unroll
            for (int i = 0; i < 4; i++) {
                const uint32_t off = (tid + 256 * i) * 32;
                uint32_t w = lds32(sb + R_A + off);
                if ((w & 1u) != tag) {
                    int it = 0;
                    uint4 x, y;
                    do { x = ld_relaxed4((const char*)g_qabs + off); y = ld_relaxed4((const char*)g_qabs + off + 16); if (++it > SPIN_LIMIT) __trap(); } while ((x.x & 1u) != tag);
                    sts128(sb + R_A + off, x.x, x.y, x.z, x.w); sts128(sb + R_A + off + 16, y.x, y.y, y.z, y.w);
                    w = x.x;
                }
                sts32(sb + R_A + off, w & ~1u);
            }
        }
        fence_async_smem();
        nbar_sync(NB_CMP, 256);
        if (tid == 0) TS(6);
        float mx[8], sum[8];
        if (E4_LL && warp >= 4) {
            const uint32_t inv = tag ^ 1u;
#pragma unroll
            for (int i = 0; i < 8; i++) sts128(sb + R_INBOX + (i * 128 + (tid & 127)) * 16, inv, inv, inv, inv);
            if (tid < 128 + 8) sts128(sb + R_STST + (tid - 128) * 16, 0, 0, 0, 0);
            fence_async_smem();
            nbar_sync(NB_G2, 128);
            if (tid == 128) {
                asm volatile("cp.async.bulk.tensor.4d.global.shared::cta.tile.bulk_group [%0, {%1, %2, %3, %4}], [%5];"
                             ::"l"(&tm_op), "r"(0), "r"(b >> 1), "r"(b & 1), "r"(0), "r"(sb + R_INBOX) : "memory");
                asm volatile("cp.async.bulk.tensor.4d.global.shared::cta.tile.bulk_group [%0, {%1, %2, %3, %4}], [%5];"
                             ::"l"(&tm_st), "r"(0), "r"(b >> 1), "r"(b & 1), "r"(0), "r"(sb + R_STST) : "memory");
                asm volatile("cp.async.bulk.commit_group;" ::: "memory");
                asm volatile("cp.async.bulk.wait_group.read 0;" ::: "memory");
                mbar_arrive(BAR(B_RST));
                asm volatile("cp.async.bulk.wait_group 0;" ::: "memory");
            }
        }
        if (warp < 4) {
            float s4[4][16];
#pragma unroll
            for (int a = 0; a < 4; a++)
#pragma unroll
                for (int i = 0; i < 16; i++) s4[a][i] = 0.f;
            const uint64_t da0 = make_desc(sb + R_C, 16, CKV_GS), db0 = make_desc(sb + R_A, 16, 1024);

            if (CKV_CONTIG) { mbar_wait(BAR(B_CKV0)); mbar_wait(BAR(B_CKV1)); mbar_wait(BAR(B_CKV2)); }
#pragma unroll
            for (int k = 0; k < 4; k++) {
                if (!CKV_CONTIG || k == 0) mbar_wait(BAR(CKV_CONTIG ? B_CKV3 : B_CKV0 + k));
                wg_fence();
#pragma unroll
                for (int u = 0; u < 8; u++) {
                    const int blk = 2 * k + (u >> 2), ks = u & 3;
                    wgmma_n32<0>(s4[ks], desc_add(da0, blk * CKV_BS + ks * 32), desc_add(db0, blk * 4096 + ks * 32), (k | (u >> 2)) != 0);
                }
                wg_commit();
            }
            wg_wait0();
            float s[16];
#pragma unroll
            for (int i = 0; i < 16; i++) s[i] = (s4[0][i] + s4[1][i]) + (s4[2][i] + s4[3][i]);
            if (lane == 0) mbar_arrive(BAR(B_FREEA));
            if (tid == 0) TS(7);
#pragma unroll
            for (int i = 0; i < 4; i++) {
                mx[2 * i] = fmaxf(s[4 * i], s[4 * i + 2]);
                mx[2 * i + 1] = fmaxf(s[4 * i + 1], s[4 * i + 3]);
            }
#pragma unroll
            for (int o = 4; o <= 16; o <<= 1)
#pragma unroll
                for (int i = 0; i < 8; i++) mx[i] = fmaxf(mx[i], __shfl_xor_sync(0xffffffffu, mx[i], o));
            if (g8 == 0) {
#pragma unroll
                for (int i = 0; i < 4; i++) {
                    stsf(sb + R_SMAX + (warp * 32 + 8 * i + 2 * q4) * 4, mx[2 * i]);
                    stsf(sb + R_SMAX + (warp * 32 + 8 * i + 2 * q4 + 1) * 4, mx[2 * i + 1]);
                }
            }
            nbar_sync(NB_WG0, 128);
#pragma unroll
            for (int i = 0; i < 4; i++) {
                float2 m0 = ldsf2(sb + R_SMAX + (0 * 32 + 8 * i + 2 * q4) * 4), m1 = ldsf2(sb + R_SMAX + (1 * 32 + 8 * i + 2 * q4) * 4);
                float2 m2 = ldsf2(sb + R_SMAX + (2 * 32 + 8 * i + 2 * q4) * 4), m3 = ldsf2(sb + R_SMAX + (3 * 32 + 8 * i + 2 * q4) * 4);
                mx[2 * i] = fmaxf(fmaxf(m0.x, m1.x), fmaxf(m2.x, m3.x));
                mx[2 * i + 1] = fmaxf(fmaxf(m0.y, m1.y), fmaxf(m2.y, m3.y));
            }
            if (E4_LL && warp == 0) mbar_wait(BAR(B_RST));
            if (warp == 0 && g8 == 0) {
                const uint32_t peer = (b & 1) ^ 1, rb = mapa(BAR(B_ST), peer);
#pragma unroll
                for (int i = 0; i < 8; i++) {
                    const uint32_t a = sb + R_ST + (8 * (i >> 1) + 2 * q4 + (i & 1)) * 4;
                    stsf(a, mx[i]);
                    st_async_f32(mapa(a + 256, peer), mx[i], rb);
                }
            }
            uint32_t pk[8];
#pragma unroll
            for (int i = 0; i < 4; i++) {
                uint32_t w0 = pack_bf16(ex2(s[4 * i] - mx[2 * i]), ex2(s[4 * i + 1] - mx[2 * i + 1]));
                uint32_t w1 = pack_bf16(ex2(s[4 * i + 2] - mx[2 * i]), ex2(s[4 * i + 3] - mx[2 * i + 1]));
                pk[i] = w0; pk[4 + i] = w1;
                sum[2 * i] = bf16lo(w0) + bf16lo(w1);
                sum[2 * i + 1] = bf16hi(w0) + bf16hi(w1);
            }
            const int head = lane;
            uint32_t a = sb + R_P + head * 128;
            stsm4t(a + (((2 * warp) ^ (head & 7)) << 4), pk[0], pk[1], pk[2], pk[3]);
            stsm4t(a + (((2 * warp + 1) ^ (head & 7)) << 4), pk[4], pk[5], pk[6], pk[7]);
            fence_async_smem();
        }
        nbar_sync(NB_CMP, 256);
        if (tid == 0) TS(8);
        {
            const int wg = __shfl_sync(0xffffffffu, warp >> 2, 0), w = warp & 3;
            const int rk = b & 1;
            const uint64_t db0 = make_desc(sb + R_P, 16, 1024);
            const uint64_t das = make_desc(sb + R_C + (4 * (rk ^ 1) + 2 * wg) * CKV_BS, CKV_GS, CKV_GS);
            const uint64_t dak = make_desc(sb + R_C + (4 * rk + 2 * wg) * CKV_BS, CKV_GS, CKV_GS);
            float os[2][16], ok_[2][16];
            wg_fence();
#pragma unroll
            for (int ks = 0; ks < 4; ks++)
#pragma unroll
                for (int t = 0; t < 2; t++) wgmma_n32<1>(os[t], desc_add(das, t * CKV_BS + ks * 2 * CKV_GS), desc_add(db0, ks * 32), ks != 0);
            wg_commit();
#pragma unroll
            for (int ks = 0; ks < 4; ks++)
#pragma unroll
                for (int t = 0; t < 2; t++) wgmma_n32<1>(ok_[t], desc_add(dak, t * CKV_BS + ks * 2 * CKV_GS), desc_add(db0, ks * 32), ks != 0);
            wg_commit();
            if (warp < 4) {
#pragma unroll
                for (int of = 4; of <= 16; of <<= 1)
#pragma unroll
                    for (int i = 0; i < 8; i++) sum[i] += __shfl_xor_sync(0xffffffffu, sum[i], of);
                if (g8 == 0) {
#pragma unroll
                    for (int i = 0; i < 4; i++) {
                        stsf(sb + R_SSUM + (warp * 32 + 8 * i + 2 * q4) * 4, sum[2 * i]);
                        stsf(sb + R_SSUM + (warp * 32 + 8 * i + 2 * q4 + 1) * 4, sum[2 * i + 1]);
                    }
                }
                nbar_sync(NB_WG0, 128);
                if (warp == 0) {
                    const uint32_t a = sb + R_SSUM + lane * 4;
                    const float l = (ldsf(a) + ldsf(a + 128)) + (ldsf(a + 256) + ldsf(a + 384));
                    const uint32_t d = sb + R_ST + 128 + lane * 4, peer = rk ^ 1;
                    stsf(d, l);
                    st_async_f32(mapa(d + 256, peer), l, mapa(BAR(B_SL), peer));
                }
            }
            mbar_wait_cluster(BAR(B_ST));
            float f[8];
#pragma unroll
            for (int i = 0; i < 4; i++) {
                const float2 mo = ldsf2(sb + R_ST + (8 * i + 2 * q4) * 4), mp = ldsf2(sb + R_ST + 256 + (8 * i + 2 * q4) * 4);
                f[2 * i] = ex2(mo.x - fmaxf(mo.x, mp.x)); f[2 * i + 1] = ex2(mo.y - fmaxf(mo.y, mp.y));
            }
            asm volatile("wgmma.wait_group.sync.aligned 1;" ::: "memory");
            {
                const uint32_t peer = rk ^ 1, dst = mapa(sb + R_INBOX + tid * 16, peer), rb = mapa(BAR(B_IN), peer);
#pragma unroll
                for (int t = 0; t < 2; t++)
#pragma unroll
                    for (int ih = 0; ih < 2; ih++) {
                        uint32_t wd[4];
#pragma unroll
                        for (int k = 0; k < 4; k++) {
                            const int i = 2 * ih + (k >> 1), e = k & 1;
                            wd[k] = pack_bf16(os[t][4 * i + e] * f[2 * i + e], os[t][4 * i + 2 + e] * f[2 * i + e]);
                        }
                        st_async_v4(dst + (2 * t + ih) * 4096, wd[0], wd[1], wd[2], wd[3], rb);
                    }
            }
            wg_wait0();
            if (lane == 0) mbar_arrive(BAR(B_FREEC));
            if (tid == 0) TS(9);
            if (warp == 7) {
                nbar_sync(NB_G2, 64);
                mbar_wait_cluster(BAR(B_SL));
                const uint32_t a = sb + R_ST + lane * 4;
                const float mo = ldsf(a), lo = ldsf(a + 128), mp = ldsf(a + 256), lp = ldsf(a + 384), m = fmaxf(mo, mp);
                if (((lane >> 2) & 1) == rk)
                    sts64(sb + R_STST + (lane >> 3) * 32 + (lane & 3) * 8, tagf(m, tag), tagf(lo * ex2(mo - m) + lp * ex2(mp - m), tag));
            } else if (warp == 0) nbar_arrive(NB_G2, 64);
            mbar_wait_cluster(BAR(B_IN));
            uint4 pv[4];
#pragma unroll
            for (int j = 0; j < 4; j++) pv[j] = lds128(sb + R_INBOX + j * 4096 + tid * 16);
            nbar_sync(NB_CMP, 256);
#pragma unroll
            for (int t = 0; t < 2; t++)
#pragma unroll
                for (int ih = 0; ih < 2; ih++) {
                    const uint32_t wd[4] = {pv[2 * t + ih].x, pv[2 * t + ih].y, pv[2 * t + ih].z, pv[2 * t + ih].w};
#pragma unroll
                    for (int k = 0; k < 4; k++) {
                        const int i = 2 * ih + (k >> 1), e = k & 1;
                        sts32(sb + R_INBOX + (8 * i + 2 * q4 + e) * 512 + ((2 * wg + t) * 32 + ((w + q4) & 3) * 8 + g8) * 4,
                              pack_tagged(fmaf(ok_[t][4 * i + e], f[2 * i + e], bf16lo(wd[k])), fmaf(ok_[t][4 * i + 2 + e], f[2 * i + e], bf16hi(wd[k])), tag));
                    }
                }
            fence_async_smem();
            nbar_arrive(NB_G3, 288);
            mbar_wait(BAR(B_WUV));
        }
        if (tid == 0) TS(10);
        uint32_t cf[8][4];
        {
            const int h = b >> 2;
            {
                const uint32_t aa = sb + R_V + (128 * (warp >> 2) + (mi >> 1) * 8 + r8) * 128 + (((2 * (warp & 3) + (mi & 1)) ^ r8) << 4);
#pragma unroll
                for (int s = 0; s < 8; s++) ldsm4t(aa + s * 2048, cf[s][0], cf[s][1], cf[s][2], cf[s][3]);
            }
            uint4 v[8]; uint2 st[8];
            {
                bool ok = lane >= 8;
                const uint32_t* fl = (const uint32_t*)(g_flagB + ((b & (FREP - 1)) * 128 + 2 * (warp * 8 + (lane & 7)) + (b & 1)) * 2);
                const uint32_t* fl2 = (const uint32_t*)(g_flagB + ((b & (FREP - 1)) * 128 + 2 * (warp * 8 + (lane & 7)) + ((h >> 2) & 1)) * 2);
                bool ok2 = lane >= 8;
                int it = 0;
                while (true) {
                    if (!ok) ok = ld_relaxed(fl) == fval;
                    if (!ok2) ok2 = ld_relaxed(fl2) == fval;
                    if (__all_sync(0xffffffffu, ok && ok2)) break;
                    if (++it > SPIN_LIMIT) __trap();
                }
            }
            if (lane == 0) mbar_arrive(BAR(B_FS));
            if (tid == 0) TS(15);
            {
                const uint4* src = g_opart + ((size_t)(2 * h + (b & 1)) * 64 + warp * 8) * 32 + lane;
                const uint2* ssrc = (const uint2*)g_stats + ((h >> 2) * 64 + warp * 8) * 4 + (h & 3);
                int it = 0;
                while (true) {
#pragma unroll
                    for (int r = 0; r < 8; r++) { v[r] = ld_relaxed4(src + r * 32); st[r] = ld_relaxed2(ssrc + r * 4); }
                    bool ok = true;
#pragma unroll
                    for (int r = 0; r < 8; r++) ok = ok && tags1_ok(v[r], tag) && (((st[r].x ^ (tag | 2u)) | (st[r].y ^ (tag | 2u))) & 3u) == 0;
                    if (__all_sync(0xffffffffu, ok)) break;
                    if (++it > SPIN_LIMIT) __trap();
                }
            }
            if (lane == 0) mbar_arrive(BAR(B_E4));
            if (tid == 0) TS(11);
            float m = untag(st[0].x);
#pragma unroll
            for (int r = 1; r < 8; r++) m = fmaxf(m, untag(st[r].x));
            float acc[8] = {}, l = 0.f;
#pragma unroll
            for (int r = 0; r < 8; r++) {
                const float wt = ex2(untag(st[r].x) - m);
                l = fmaf(wt, untag(st[r].y), l);
                acc[0] = fmaf(wt, bf16lo(v[r].x & ~1u), acc[0]); acc[1] = fmaf(wt, bf16hi(v[r].x), acc[1]);
                acc[2] = fmaf(wt, bf16lo(v[r].y & ~1u), acc[2]); acc[3] = fmaf(wt, bf16hi(v[r].y), acc[3]);
                acc[4] = fmaf(wt, bf16lo(v[r].z & ~1u), acc[4]); acc[5] = fmaf(wt, bf16hi(v[r].z), acc[5]);
                acc[6] = fmaf(wt, bf16lo(v[r].w & ~1u), acc[6]); acc[7] = fmaf(wt, bf16hi(v[r].w), acc[7]);
            }
            {
                const uint32_t a = sb + R_P + warp * 1024 + lane * 16;
                sts128(a, __float_as_uint(acc[0]), __float_as_uint(acc[1]), __float_as_uint(acc[2]), __float_as_uint(acc[3]));
                sts128(a + 512, __float_as_uint(acc[4]), __float_as_uint(acc[5]), __float_as_uint(acc[6]), __float_as_uint(acc[7]));
                if (lane == 0) sts64(sb + R_WTS + warp * 8, __float_as_uint(m), __float_as_uint(l));
            }
            nbar_sync(NB_CMP, 256);
            {
                float2 ml[8];
                float M = -INFINITY;
#pragma unroll
                for (int w = 0; w < 8; w++) { ml[w] = ldsf2(sb + R_WTS + w * 8); M = fmaxf(M, ml[w].x); }
                float sacc = 0.f, L = 0.f;
#pragma unroll
                for (int w = 0; w < 8; w++) {
                    const float sc = ex2(ml[w].x - M);
                    L = fmaf(sc, ml[w].y, L);
                    sacc = fmaf(sc, ldsf(sb + R_P + w * 1024 + tid * 4), sacc);
                }
                const int u = (tid >> 2) & 31, k = 4 * (tid >> 7) + (tid & 3), pos = 4 * u + (k >> 1);
                const int c = 64 * (pos >> 5) + 16 * ((((pos >> 3) & 3) - (h >> 1)) & 3) + (pos & 7) + 8 * (k & 1);
                sts_hilo(sb + R_VO + c * 2, VO_LO, __fdividef(sacc, L));
            }
            nbar_sync(NB_CMP, 256);
        }
        if (tid == 0) TS(12);
        {
            int kb; uint32_t ba = bvec_addr(sb + R_VO + (warp >> 2) * 256, VO_LO, zero, lane, kb);
            float acc[2][4] = {};
#pragma unroll
            for (int s = 0; s < 8; s++) {
                uint32_t b0, b1;
                ldsm2(ba + s * kb, b0, b1);
                mma16816(acc[s & 1], cf[s][0], cf[s][1], cf[s][2], cf[s][3], b0, b1);
            }
            if (q4 == 0) {
                const float v0 = (acc[0][0] + acc[0][1]) + (acc[1][0] + acc[1][1]), v1 = (acc[0][2] + acc[0][3]) + (acc[1][2] + acc[1][3]);
                const uint32_t xq = sb + R_XQP + ((warp >> 2) * 64 + (warp & 3) * 16 + g8) * 4;
                const uint32_t rq = mapa(xq + 512, (b & 1) ^ 1), rb = mapa(BAR(B_XC), (b & 1) ^ 1);
                st_async_f32(rq, v0, rb);
                st_async_f32(rq + 32, v1, rb);
                stsf(xq, v0); stsf(xq + 32, v1);
            }
        }
        if (tid == 0) TS(14);
        {
            uint32_t af[2][2][4][4];
            const bool two = (b & 1) == 0 && warp < 2;
            mbar_wait(BAR(B_WO));
            {
                const uint32_t base = sb + R_O + (warp >> 1) * 8192 + ((mi >> 1) * 8 + r8) * 128;
                const int cc = (warp & 1) * 4 + (mi & 1);
                const uint32_t a0 = base + ((cc ^ r8) << 4), a1 = base + (((cc + 2) ^ r8) << 4);
#pragma unroll
                for (int pi = 0; pi < 2; pi++)
                    if (pi == 0 || two) {
#pragma unroll
                        for (int s = 0; s < 4; s++) {
                            ldsm4t(a0 + pi * 32768 + s * 2048, af[pi][0][s][0], af[pi][0][s][1], af[pi][0][s][2], af[pi][0][s][3]);
                            ldsm4t(a1 + pi * 32768 + s * 2048, af[pi][1][s][0], af[pi][1][s][1], af[pi][1][s][2], af[pi][1][s][3]);
                        }
                    }
            }
            nbar_sync(NB_CMP, 256);
            mbar_wait_cluster(BAR(B_XC));
            if (tid < 64) {
                const uint32_t xq = sb + R_XQP + tid * 4;
                sts_hilo(sb + R_VC + tid * 2, VC_LO, (ldsf(xq) + ldsf(xq + 256)) + (ldsf(xq + 512) + ldsf(xq + 768)));
            }
            nbar_sync(NB_CMP, 256);
            if (tid == 0) TS(49);
            int kb; uint32_t ba = bvec_addr(sb + R_VC, VC_LO, zero, lane, kb);
            float acc[2][2][4] = {};
#pragma unroll
            for (int s = 0; s < 4; s++) {
                uint32_t b0, b1;
                ldsm2(ba + s * kb, b0, b1);
#pragma unroll
                for (int pi = 0; pi < 2; pi++)
                    if (pi == 0 || two) {
                        mma16816(acc[pi][0], af[pi][0][s][0], af[pi][0][s][1], af[pi][0][s][2], af[pi][0][s][3], b0, b1);
                        mma16816(acc[pi][1], af[pi][1][s][0], af[pi][1][s][1], af[pi][1][s][2], af[pi][1][s][3], b0, b1);
                    }
            }
            const int src = lane & ~3;
            uint32_t* dst = (uint32_t*)g_pE6 + ((10 * (b & 1) + warp) * 64 + (b >> 1)) * 32 + 8 * q4 + g8;
#pragma unroll
            for (int pi = 0; pi < 2; pi++)
                if (pi == 0 || two) {
                    const float v0 = __shfl_sync(0xffffffffu, acc[pi][0][0] + acc[pi][0][1], src), v1 = __shfl_sync(0xffffffffu, acc[pi][0][2] + acc[pi][0][3], src);
                    const float v2 = __shfl_sync(0xffffffffu, acc[pi][1][0] + acc[pi][1][1], src), v3 = __shfl_sync(0xffffffffu, acc[pi][1][2] + acc[pi][1][3], src);
                    xchg_word(dst + pi * (8 * 64 * 32), tagf(q4 == 0 ? v0 : q4 == 1 ? v1 : q4 == 2 ? v2 : v3, tag));
                }
        }
        if (lane == 0) mbar_arrive(BAR(B_DD));
        if (b < NFFN) nbar_arrive(NB_G1, 288);
        if (tid == 0) TS(16);
        if (b >= NFFN && b < NFFN + 18) {
            const int p = b - NFFN;
            const float xres = __bfloat162float(prm.x[32 * p + lane]);
            const float hcol = xres + cta_reduce32<64>(g_pE6 + p * 512, sb + R_RED, tag, warp, lane, sb, 34);
            if (warp < HREP) xchg_word((uint32_t*)g_hbuf + warp * 576 + 32 * p + lane, tagf(hcol, tag));
            if (tid == 0) TS(21);
            const float f = cta_reduce32<NFFN>(g_pE8 + p * 1024, sb + R_RED + 1024, tag, warp, lane, sb, 37);
            if (warp == 0) {
                prm.out[32 * p + lane] = __float2bfloat16_rn(hcol + f);
                if (p == 0 && lane == 0) st_relaxed(&g_epoch, lds32(sb + R_TAG + 4));
            }
            if (tid == 0) TS(22);
        }
        if (b < NFFN) {
            uint32_t gf[3][2][3][4];
            {
                const uint32_t aa = sb + R_A + ((mi >> 1) * 8 + r8) * 96 + (mi & 1) * 16 + warp * 1536;
                uint32_t af[5][3][4];
                if (!EXP_NOJIT) mbar_wait(BAR(B_W1));
#pragma unroll
                for (int k = 0; k < 5; k++) {
                    if (k < 4 || warp < 4) {
#pragma unroll
                        for (int mt = 0; mt < 3; mt++) ldsm4t(aa + k * 12288 + mt * 32, af[k][mt][0], af[k][mt][1], af[k][mt][2], af[k][mt][3]);
                    }
                }
                {
                    const uint32_t one = (lane >> 2) == 0 ? 0x3f803f80u : 0u;
                    float cs[3][4] = {};
#pragma unroll
                    for (int k = 0; k < 5; k++)
                        if (k < 4 || warp < 4) {
#pragma unroll
                            for (int mt = 0; mt < 3; mt++) mma16816(cs[mt], af[k][mt][0], af[k][mt][1], af[k][mt][2], af[k][mt][3], one, one);
                        }
                    if (q4 == 0) {
#pragma unroll
                        for (int mt = 0; mt < 3; mt++) {
                            stsf(sb + R_RED + 2048 + (warp * 48 + mt * 16 + g8) * 4, cs[mt][0]);
                            stsf(sb + R_RED + 2048 + (warp * 48 + mt * 16 + g8 + 8) * 4, cs[mt][2]);
                        }
                    }
                }
                if (G_EARLY) { if (!EXP_NOJIT) mbar_wait(BAR(B_W2)); frag576_load<3>(gf, sb + R_C, warp, lane); }
                int kb; uint32_t ba = bvec_addr(sb + R_VH, VH_LO, zero, lane, kb);
                ba += warp * kb;
                nbar_sync(NB_VEC, 288);
                if (tid == 0) TS(17);
                float acc[2][3][4] = {};
#pragma unroll
                for (int k = 0; k < 5; k++) {
                    if (k < 4 || warp < 4) {
                        uint32_t b0, b1;
                        ldsm2(ba + k * 8 * kb, b0, b1);
#pragma unroll
                        for (int mt = 0; mt < 3; mt++) mma16816(acc[k & 1][mt], af[k][mt][0], af[k][mt][1], af[k][mt][2], af[k][mt][3], b0, b1);
                    }
                }
                if (q4 == 0) {
#pragma unroll
                    for (int mt = 0; mt < 3; mt++) {
                        stsf(sb + R_RED + 512 + (warp * 48 + mt * 16 + g8) * 4, (acc[0][mt][0] + acc[0][mt][1]) + (acc[1][mt][0] + acc[1][mt][1]));
                        stsf(sb + R_RED + 512 + (warp * 48 + mt * 16 + g8 + 8) * 4, (acc[0][mt][2] + acc[0][mt][3]) + (acc[1][mt][2] + acc[1][mt][3]));
                    }
                }
            }
            nbar_sync(NB_CMP, 256);
            if (warp >= 6) {
                const int i = tid - 208;
                float a = 0.f, cs = 0.f;
                if (i >= 0) {
#pragma unroll
                    for (int w = 0; w < 8; w++) { a += ldsf(sb + R_RED + 512 + (w * 48 + i) * 4); cs += ldsf(sb + R_RED + 2048 + (w * 48 + i) * 4); }
                }
                nbar_sync(NB_G2, 96);
                if (i >= 0) {
                    const float2 mr = ldsf2(sb + R_WTS + 128);
                    a = mr.y * fmaf(-mr.x, cs, a);
                    sts_hilo(sb + R_VU + i * 2, VU_LO, __fdividef(a, 1.f + __expf(-a)));
                }
            }
            if (!G_EARLY) { if (!EXP_NOJIT) mbar_wait(BAR(B_W2)); frag576_load<3>(gf, sb + R_C, warp, lane); }
            nbar_sync(NB_CMP, 256);
            if (tid == 0) TS(18);
            gemv576_finish<3>(gf, sb + R_VU, VU_LO, zero, g_pE8, b, tag, warp, lane);
            if (tid == 0) TS(19);
        }
    } else if (warp == 8) {
        if (lane == 0) {
            uint32_t t16 = START_OFF * 16 + 9 * pace16(4096);
            if (PF_AHEAD) {
                t16 += 4 * pace16(8192);
                int kw = 0, kc = 0;
#pragma unroll 1
                while (kw < 4 || kc < 8) {
                    const uint32_t tw = kw < 4 ? START_OFF * 16 + (9 + 2 * (b & 3) + (kw >> 1)) * pace16(4096) + LAG0_NS * 16 : 0xffffffffu;
                    const uint32_t tc = kc < 8 ? t16 : 0xffffffffu;
                    if (tw <= tc) {
                        pace_until(g0, tw);
                        tma3(sb + R_A + R_A_WUK + kw * 8192, &tm_wuk, 0, 128 * (b & 3) + 32 * kw, 2 * (b >> 2), BAR(B_WUK));
                        kw++;
                    } else {
                        pace_until(g0, tc);
                        tma3(sb + R_C + kc * 8192, &tm_ckv, 0, 64 * b + 8 * kc, 0, BAR(B_CKV0 + (kc >> 1)));
                        t16 += pace16(8192);
                        kc++;
                    }
                }
            } else {
#pragma unroll 1
                for (int k = 0; k < 4; k++) { pace_until(g0, t16); tma3(sb + R_A + R_A_WUK + k * 8192, &tm_wuk, 0, 128 * (b & 3) + 32 * k, 2 * (b >> 2), BAR(B_WUK)); t16 += pace16(8192); }
#pragma unroll 1
                for (int k = 0; k < 8; k++) {
                    pace_until(g0, t16);
                    if (CKV_CONTIG) tma3(sb + R_C + k * 8192, &tm_ckv, 0, 64 * b + 8 * k, 0, BAR(B_CKV0 + (k >> 1)));
                    else tma3(sb + R_C + k * 8192, &tm_ckv, 0, 64 * b, k, BAR(B_CKV0 + (k >> 1)));
                    t16 += pace16(8192);
                }
            }
#pragma unroll 1
            for (int k = 0; k < 4; k++) { pace_until(g0, t16); tma3(sb + R_V + k * 8192, &tm_wuv, 0, 256 * (b & 1) + 64 * k, b >> 1, BAR(B_WUV)); t16 += pace16(8192); }
#pragma unroll 1
            for (int k = 0; k < 5 - (b & 1); k++) { pace_until(g0, t16); tma3(sb + R_O + k * 8192, &tm_wo, 0, 64 * (b >> 1), 5 * (b & 1) + k, BAR(B_WO)); t16 += (b & 1) ? pace2_16(9216) : pace2_16(36864 / 5); }
#pragma unroll 1
            for (int k = 0; k < 9; k++) { pace_until(g0, t16); l2_prefetch(prm.w1 + (size_t)(k * 128 + b) * 4608, 4608); t16 += pace2_16(4608); }
#pragma unroll 1
            for (int k = 0; k < 9; k++) { pace_until(g0, t16); l2_prefetch(prm.w2 + (size_t)(k * 128 + b) * 4608, 4608); t16 += pace2_16(4608); }
            TS(20);
        }
    } else if (warp == 9) {
        const uint32_t tag = (epoch + 1u) & 1u;
        if (b < NFFN) {
            nbar_sync(NB_G1, 288);
            if (lane == 0) TS(50);
            const uint4* src = g_hbuf + (b & (HREP - 1)) * 144;
            uint4 v[5];
            int it = 0;
            uint32_t pend = lane < 16 ? 0x1fu : 0xfu;
            while (true) {
#pragma unroll
                for (int k = 0; k < 5; k++) if (pend & (1u << k)) v[k] = ld_relaxed4(src + 32 * k + lane);
#pragma unroll
                for (int k = 0; k < 5; k++) if ((pend & (1u << k)) && tags_ok(v[k], tag)) pend &= ~(1u << k);
                if (__all_sync(0xffffffffu, pend == 0)) break;
                if (++it > SPIN_LIMIT) __trap();
            }
            if (lane == 0) { mbar_arrive(BAR(B_HL)); TS(51); }
#pragma unroll
            for (int k = 0; k < 5; k++) {
                if (k < 4 || lane < 16) {
                    uint32_t h0, l0, h1, l1;
                    hilo2(untag(v[k].x), untag(v[k].y), h0, l0);
                    hilo2(untag(v[k].z), untag(v[k].w), h1, l1);
                    sts64(sb + R_VH + (32 * k + lane) * 8, h0, h1);
                    sts64(sb + R_VH + VH_LO + (32 * k + lane) * 8, l0, l1);
                }
            }
            nbar_arrive(NB_VEC, 288);
            const float pivot = __shfl_sync(0xffffffffu, untag(v[0].x), 0);
            float sum = 0.f, sq = 0.f;
#pragma unroll
            for (int k = 0; k < 5; k++) {
                if (k < 4 || lane < 16) {
                    const float d0 = untag(v[k].x) - pivot, d1 = untag(v[k].y) - pivot, d2 = untag(v[k].z) - pivot, d3 = untag(v[k].w) - pivot;
                    sum += (d0 + d1) + (d2 + d3);
                    sq = fmaf(d0, d0, fmaf(d1, d1, fmaf(d2, d2, fmaf(d3, d3, sq))));
                }
            }
#pragma unroll
            for (int o = 16; o; o >>= 1) { sum += __shfl_xor_sync(0xffffffffu, sum, o); sq += __shfl_xor_sync(0xffffffffu, sq, o); }
            const float dm = sum * (1.f / 576.f);
            if (lane == 0) sts64(sb + R_WTS + 128, __float_as_uint(pivot + dm), __float_as_uint(rsqrtf(fmaxf(sq * (1.f / 576.f) - dm * dm, 0.f) + 1e-5f)));
            nbar_arrive(NB_G2, 96);
        }
    } else {
        if (warp == 11) {
            nbar_sync(NB_G3, 288);
            if (lane == 0) {
                asm volatile("cp.async.bulk.tensor.4d.global.shared::cta.tile.bulk_group [%0, {%1, %2, %3, %4}], [%5];"
                             ::"l"(&tm_st), "r"(0), "r"(b >> 1), "r"(b & 1), "r"(0), "r"(sb + R_STST) : "memory");
                asm volatile("cp.async.bulk.tensor.4d.global.shared::cta.tile.bulk_group [%0, {%1, %2, %3, %4}], [%5];"
                             ::"l"(&tm_op), "r"(0), "r"(b >> 1), "r"(b & 1), "r"(0), "r"(sb + R_INBOX) : "memory");
                asm volatile("cp.async.bulk.commit_group;" ::: "memory");
                delay_ns(FLAG_DELAY);
                TS(33);
            }
            __syncwarp();
            const uint32_t fv = epoch + 1u;
            if (!E4_LL && lane < FREP) red_max((unsigned*)(g_flagB + (lane * 128 + b) * 2), fv);
            if (lane == 0) {
                if (EARLY_FLAG == 2) asm volatile("cp.async.bulk.wait_group.read 0;" ::: "memory");
                TS(60);
                if (b < NFFN && !EXP_NOJIT) {
                    mbar_wait(BAR(B_FREEC));
                    mbar_wait(BAR(B_E4));
                    unsigned g1 = gtime();
                    uint32_t t16 = 0;
#pragma unroll 1
                    for (int k = 0; k < 12; k++) {
                        if (k == JIT_PAUSE_AT) { mbar_wait(BAR(B_DD)); g1 = gtime(); t16 = JIT2_DELAY * 16; }
                        if (k == 6 && JIT2_GATE == 1) { mbar_wait(BAR(B_HL)); g1 = gtime(); t16 = 0; }
                        if (k == 6 && JIT2_GATE == 2) { mbar_wait(BAR(B_DD)); g1 = gtime(); t16 = JIT2_DELAY * 16; }
                        pace_until(g1, t16);
                        if (k >= 6) tma3(sb + R_C + (k - 6) * 9216, &tm_w2, 0, 48 * b + 8 * (k - 6), 0, BAR(B_W2));
                        else if (k < W1_TMA_BOXES) tma2(sb + R_A + k * 9216, &tm_w1, 48 * b, 96 * k, BAR(B_W1));
                        t16 += k < 6 ? (k < W1_TMA_BOXES ? jit16(9216, NFFN) : 0u) : (uint32_t)((uint64_t)9216 * NFFN * 16u / JIT2_GBS);
                    }
                }
                asm volatile("cp.async.bulk.wait_group 0;" ::: "memory");
                TS(61);
            }
        }
        if (W1_TMA_BOXES < 6 && warp == 10 && b < NFFN) {
            const char* src = prm.w1 + 96 * b;
            int row = 96 * W1_TMA_BOXES + lane / 6, cc = lane % 6;
            mbar_wait(BAR(B_E4));
#pragma unroll 6
            for (int i = 0; i < 18 * (6 - W1_TMA_BOXES); i++) {
                cp_async16(sb + R_A + (row * 6 + cc) * 16, src + (size_t)row * 9216 + cc * 16);
                row += 5; cc += 2;
                if (cc >= 6) { cc -= 6; row++; }
            }
            cp_async_arrive(BAR(B_W1));
        }
    }
}

typedef CUresult (*EncodeTiledFn)(CUtensorMap*, CUtensorMapDataType, cuuint32_t, void*, const cuuint64_t*, const cuuint64_t*,
                                  const cuuint32_t*, const cuuint32_t*, CUtensorMapInterleave, CUtensorMapSwizzle,
                                  CUtensorMapL2promotion, CUtensorMapFloatOOBfill);

bool make_map(EncodeTiledFn fn, CUtensorMap* m, const void* base, int rank, const cuuint64_t* dims, const cuuint64_t* strides,
              const cuuint32_t* box, CUtensorMapSwizzle sw) {
    cuuint32_t es[3] = {1, 1, 1};
    return fn(m, CU_TENSOR_MAP_DATA_TYPE_BFLOAT16, rank, const_cast<void*>(base), dims, strides, box, es,
              CU_TENSOR_MAP_INTERLEAVE_NONE, sw, (CUtensorMapL2promotion)L2PROMO, CU_TENSOR_MAP_FLOAT_OOB_FILL_NONE) == CUDA_SUCCESS;
}

}

extern "C" void kernel_launch(void* const* d_in, const int* in_sizes, int n_in, void* d_out, int out_size) {
    (void)in_sizes; (void)n_in; (void)out_size;
    static EncodeTiledFn encode = nullptr;
    if (!encode) {
        void* fn = nullptr;
        cudaDriverEntryPointQueryResult qr;
        cudaGetDriverEntryPoint("cuTensorMapEncodeTiled", &fn, cudaEnableDefault, &qr);
        encode = (EncodeTiledFn)fn;
        cudaFuncSetAttribute(fused_decode_kernel, cudaFuncAttributeMaxDynamicSharedMemorySize, SMEM_BYTES);
    }
    CUtensorMap tm_op, tm_st, tm_wuk, tm_ckv, tm_wuv, tm_wo, tm_w1, tm_w2;
    {
        void* op = nullptr;
        cudaGetSymbolAddress(&op, g_opart);
        cuuint64_t d[4] = {128, 64, 2, 32}, s[3] = {512, 32768, 65536}; cuuint32_t bx[4] = {128, 1, 1, 32}, es[4] = {1, 1, 1, 1};
        encode(&tm_op, CU_TENSOR_MAP_DATA_TYPE_UINT32, 4, op, d, s, bx, es, CU_TENSOR_MAP_INTERLEAVE_NONE, CU_TENSOR_MAP_SWIZZLE_NONE,
               CU_TENSOR_MAP_L2_PROMOTION_NONE, CU_TENSOR_MAP_FLOAT_OOB_FILL_NONE);
        cudaGetSymbolAddress(&op, g_stats);
        cuuint64_t d2[4] = {8, 64, 2, 4}, s2[3] = {32, 2048, 4096}; cuuint32_t bx2[4] = {8, 1, 1, 4};
        encode(&tm_st, CU_TENSOR_MAP_DATA_TYPE_UINT32, 4, op, d2, s2, bx2, es, CU_TENSOR_MAP_INTERLEAVE_NONE, CU_TENSOR_MAP_SWIZZLE_NONE,
               CU_TENSOR_MAP_L2_PROMOTION_NONE, CU_TENSOR_MAP_FLOAT_OOB_FILL_NONE);
    }
    {
        cuuint64_t d[3] = {64, 512, 64}, s[2] = {8192, 128}; cuuint32_t bx[3] = {64, 32, 2};
        make_map(encode, &tm_wuk, d_in[3], 3, d, s, bx, CU_TENSOR_MAP_SWIZZLE_128B);
    }
    {
        cuuint64_t d[3] = {64, 8192, 8}, s[2] = {1024, 128}; cuuint32_t bx[3] = {64, CKV_CONTIG ? 8u : 64u, CKV_CONTIG ? 8u : 1u};
        make_map(encode, &tm_ckv, d_in[1], 3, d, s, bx, CU_TENSOR_MAP_SWIZZLE_128B);
    }
    {
        cuuint64_t d[3] = {64, 512, 64}, s[2] = {8192, 128}; cuuint32_t bx[3] = {64, 64, 1};
        make_map(encode, &tm_wuv, d_in[4], 3, d, s, bx, CU_TENSOR_MAP_SWIZZLE_128B);
    }
    {
        cuuint64_t d[3] = {64, 4096, 9}, s[2] = {1152, 128}; cuuint32_t bx[3] = {64, 64, 1};
        make_map(encode, &tm_wo, d_in[5], 3, d, s, bx, CU_TENSOR_MAP_SWIZZLE_128B);
    }
    {
        cuuint64_t d[2] = {4608, 576}, s[1] = {9216}; cuuint32_t bx[2] = {48, 96};
        make_map(encode, &tm_w1, d_in[7], 2, d, s, bx, CU_TENSOR_MAP_SWIZZLE_NONE);
    }
    {
        cuuint64_t d[3] = {64, 4608, 9}, s[2] = {1152, 128}; cuuint32_t bx[3] = {64, 8, 9};
        make_map(encode, &tm_w2, d_in[8], 3, d, s, bx, CU_TENSOR_MAP_SWIZZLE_128B);
    }
    Params prm;
    prm.x = (const __nv_bfloat16*)d_in[0];
    prm.wq = (const __nv_bfloat16*)d_in[2];
    prm.wuk = (const char*)d_in[3];
    prm.wo = (const char*)d_in[5];
    prm.w1 = (const char*)d_in[7];
    prm.w2 = (const char*)d_in[8];
    prm.out = (__nv_bfloat16*)d_out;
    fused_decode_kernel<<<NCTA, NTHREADS, SMEM_BYTES, cudaStreamPerThread>>>(tm_op, tm_st, tm_wuk, tm_ckv, tm_wuv, tm_wo, tm_w1, tm_w2, prm);
}
```

```cpp
#include <cuda_runtime.h>
#include <cuda_bf16.h>
#include <cuda.h>
#include <stdint.h>

namespace {

constexpr int NCTA = 128;
constexpr int NFFN = 96;
constexpr int NRED = 18;
constexpr int NTHREADS = 384;
constexpr int SPIN_LIMIT = 1 << 22;

constexpr uint32_t RATE_A = 3000;
constexpr uint32_t RATE_B = 3050;
constexpr uint32_t RATE_C = 3150;
constexpr uint32_t START_NS = 100;
constexpr uint32_t W1_GBS = 2700;
constexpr uint32_t W2_GBS = 4000;
constexpr uint32_t QABS_WAIT_NS = 550;
constexpr uint32_t LATE_WAIT_NS = 400;
constexpr uint32_t FLAG_WAIT_NS = 750;
constexpr uint32_t FFN_WAIT_NS = 1400;

constexpr uint32_t R_A = 0;
constexpr uint32_t R_A_WUK = 36864;
constexpr uint32_t R_C = 71680;
constexpr uint32_t R_V = R_C + 65536;
constexpr uint32_t R_O = R_V + 32768;
constexpr uint32_t R_P = R_O + 40960;
constexpr uint32_t R_RED = R_P + 4096;
constexpr uint32_t R_VXN = R_RED + 4096;
constexpr uint32_t VXN_LO = 576 + 16;
constexpr uint32_t R_XQP = R_VXN + 1280;
constexpr uint32_t R_VQ = R_XQP + 1024;
constexpr uint32_t VQ_LO = 256 + 16;
constexpr uint32_t R_VO = R_VQ + 640;
constexpr uint32_t VO_LO = 512 + 16;
constexpr uint32_t R_VC = R_VO + 1088;
constexpr uint32_t VC_LO = 128 + 16;
constexpr uint32_t R_VH = R_VC + 320;
constexpr uint32_t VH_LO = 1152 + 16;
constexpr uint32_t R_VU = R_VH + 2432;
constexpr uint32_t VU_LO = 96 + 16;
constexpr uint32_t R_ZERO = R_VU + 256 + 64;
constexpr uint32_t R_WTS = R_VU + 384;
constexpr uint32_t R_SMAX = R_WTS + 1024;
constexpr uint32_t R_STST = R_SMAX + 512;
constexpr uint32_t R_ST = R_STST + 512;
constexpr uint32_t R_TAG = R_ST + 512;
constexpr uint32_t R_BAR = R_TAG + 64;
constexpr uint32_t SMEM_USED = R_BAR + 24 * 8;
constexpr uint32_t SMEM_BYTES = SMEM_USED + 1024;
static_assert(SMEM_BYTES <= 232448, "smem");
static_assert(R_P % 1024 == 0 && R_C % 1024 == 0 && R_V % 1024 == 0 && R_O % 1024 == 0, "align");

constexpr uint32_t R_INBOX = R_A + 55296;
static_assert(R_XQP % 128 == 0 && R_INBOX % 128 == 0 && R_STST % 128 == 0, "align");

enum { B_WQ = 0, B_WUK, B_CKV0, B_CKV1, B_CKV2, B_CKV3, B_WUV, B_WO, B_W1, B_W2, B_FS, B_FREEC, B_XQ, B_QA, B_ST, B_IN, B_XC, B_SL, B_RQ, NBAR };
enum { NB_VEC = 1, NB_CMP = 2, NB_WG0 = 3, NB_G1 = 4, NB_G2 = 5, NB_G3 = 6, NB_INIT = 7, NB_P = 8 };

__host__ __device__ constexpr uint32_t time16(uint32_t bytes, uint32_t gbs, uint32_t nctas) { return (uint32_t)((uint64_t)bytes * nctas * 16u / gbs); }
constexpr int HREP = 2;
constexpr int FREP = 4;

__device__ unsigned g_epoch;
__device__ __align__(128) uint4 g_flagB[FREP * 128 * 2];
__device__ __align__(128) uint4 g_xq[128 * 32];
__device__ __align__(1024) uint4 g_qabs[2048];
__device__ __align__(1024) uint4 g_opart[64 * 64 * 32];
__device__ __align__(1024) uint4 g_stats[8 * 64 * 2];
__device__ __align__(128) uint4 g_pE6[18 * 64 * 8];
__device__ __align__(128) uint4 g_hbuf[HREP * 144];
__device__ __align__(128) uint4 g_pE8[18 * 128 * 8];


struct Params {
    const __nv_bfloat16* x;
    const __nv_bfloat16* wq;
    const char* w1;
    const char* w2;
    __nv_bfloat16* out;
};

__device__ __forceinline__ uint32_t smem_u32(const void* p) { return (uint32_t)__cvta_generic_to_shared(p); }
__device__ __forceinline__ void mbar_init(uint32_t bar, uint32_t cnt) {
    asm volatile("mbarrier.init.shared::cta.b64 [%0], %1;" ::"r"(bar), "r"(cnt) : "memory");
}
__device__ __forceinline__ void mbar_expect_tx(uint32_t bar, uint32_t bytes) {
    asm volatile("mbarrier.arrive.expect_tx.shared::cta.b64 _, [%0], %1;" ::"r"(bar), "r"(bytes) : "memory");
}
__device__ __forceinline__ void mbar_arrive(uint32_t bar) {
    asm volatile("mbarrier.arrive.shared::cta.b64 _, [%0];" ::"r"(bar) : "memory");
}
__device__ __forceinline__ bool mbar_try(uint32_t bar, uint32_t parity) {
    uint32_t ok;
    asm volatile("{\n.reg .pred p;\nmbarrier.try_wait.parity.shared::cta.b64 p, [%1], %2;\nselp.u32 %0, 1, 0, p;\n}"
                 : "=r"(ok) : "r"(bar), "r"(parity) : "memory");
    return ok;
}
__device__ __forceinline__ void mbar_wait(uint32_t bar) {
    int it = 0;
    while (!mbar_try(bar, 0)) { if (++it > SPIN_LIMIT) __trap(); }
}
__device__ __forceinline__ void mbar_wait_cluster(uint32_t bar) {
    int it = 0;
    while (true) {
        uint32_t ok;
        asm volatile("{\n.reg .pred p;\nmbarrier.try_wait.parity.acquire.cluster.shared::cta.b64 p, [%1], 0;\nselp.u32 %0, 1, 0, p;\n}" : "=r"(ok) : "r"(bar) : "memory");
        if (ok) break;
        if (++it > SPIN_LIMIT) __trap();
    }
}
__device__ __forceinline__ uint32_t mapa(uint32_t a, uint32_t rank) { uint32_t d; asm volatile("mapa.shared::cluster.u32 %0, %1, %2;" : "=r"(d) : "r"(a), "r"(rank)); return d; }
__device__ __forceinline__ void st_async_f32(uint32_t a, float v, uint32_t bar) {
    asm volatile("st.async.weak.shared::cluster.mbarrier::complete_tx::bytes.f32 [%0], %1, [%2];" ::"r"(a), "f"(v), "r"(bar) : "memory");
}
__device__ __forceinline__ void st_async_v4(uint32_t a, uint32_t x, uint32_t y, uint32_t z, uint32_t w, uint32_t bar) {
    asm volatile("st.async.weak.shared::cluster.mbarrier::complete_tx::bytes.v4.b32 [%0], {%1,%2,%3,%4}, [%5];" ::"r"(a), "r"(x), "r"(y), "r"(z), "r"(w), "r"(bar) : "memory");
}
__device__ __forceinline__ void nbar_sync(int id, int n) { asm volatile("bar.sync %0, %1;" ::"r"(id), "r"(n) : "memory"); }
__device__ __forceinline__ void nbar_arrive(int id, int n) { asm volatile("bar.arrive %0, %1;" ::"r"(id), "r"(n) : "memory"); }
__device__ __forceinline__ void fence_async_smem() { asm volatile("fence.proxy.async.shared::cta;" ::: "memory"); }

__device__ __forceinline__ void cp_async16(uint32_t dst, const void* src) {
    asm volatile("cp.async.cg.shared.global [%0], [%1], 16;" ::"r"(dst), "l"(src) : "memory");
}
__device__ __forceinline__ void cp_async_arrive(uint32_t bar) {
    asm volatile("cp.async.mbarrier.arrive.noinc.shared::cta.b64 [%0];" ::"r"(bar) : "memory");
}
__device__ __forceinline__ uint64_t policy_evict_first() {
    uint64_t p;
    asm volatile("createpolicy.fractional.L2::evict_first.b64 %0, 1.0;" : "=l"(p));
    return p;
}
__device__ __forceinline__ void tma3(uint32_t dst, const CUtensorMap* tm, int c0, int c1, int c2, uint32_t bar, uint64_t pol) {
    asm volatile("cp.async.bulk.tensor.3d.shared::cluster.global.tile.mbarrier::complete_tx::bytes.L2::cache_hint [%0], [%1, {%2, %3, %4}], [%5], %6;"
                 ::"r"(dst), "l"(tm), "r"(c0), "r"(c1), "r"(c2), "r"(bar), "l"(pol) : "memory");
}
__device__ __forceinline__ void tma2(uint32_t dst, const CUtensorMap* tm, int c0, int c1, uint32_t bar) {
    asm volatile("cp.async.bulk.tensor.2d.shared::cluster.global.tile.mbarrier::complete_tx::bytes [%0], [%1, {%2, %3}], [%4];"
                 ::"r"(dst), "l"(tm), "r"(c0), "r"(c1), "r"(bar) : "memory");
}
__device__ __forceinline__ void l2_prefetch(const void* p, uint32_t bytes) {
    asm volatile("cp.async.bulk.prefetch.L2.global [%0], %1;" ::"l"(p), "r"(bytes) : "memory");
}
__device__ __forceinline__ void prefetch_tmap(const CUtensorMap* tm) {
    asm volatile("prefetch.tensormap [%0];" ::"l"(tm) : "memory");
}
__device__ __forceinline__ void ldsm4(uint32_t a, uint32_t& r0, uint32_t& r1, uint32_t& r2, uint32_t& r3) {
    asm volatile("ldmatrix.sync.aligned.m8n8.x4.shared.b16 {%0,%1,%2,%3}, [%4];" : "=r"(r0), "=r"(r1), "=r"(r2), "=r"(r3) : "r"(a) : "memory");
}
__device__ __forceinline__ void ldsm4t(uint32_t a, uint32_t& r0, uint32_t& r1, uint32_t& r2, uint32_t& r3) {
    asm volatile("ldmatrix.sync.aligned.m8n8.x4.trans.shared.b16 {%0,%1,%2,%3}, [%4];" : "=r"(r0), "=r"(r1), "=r"(r2), "=r"(r3) : "r"(a) : "memory");
}
__device__ __forceinline__ void ldsm2(uint32_t a, uint32_t& r0, uint32_t& r1) {
    asm volatile("ldmatrix.sync.aligned.m8n8.x2.shared.b16 {%0,%1}, [%2];" : "=r"(r0), "=r"(r1) : "r"(a) : "memory");
}
__device__ __forceinline__ void stsm4t(uint32_t a, uint32_t r0, uint32_t r1, uint32_t r2, uint32_t r3) {
    asm volatile("stmatrix.sync.aligned.m8n8.x4.trans.shared.b16 [%0], {%1,%2,%3,%4};" ::"r"(a), "r"(r0), "r"(r1), "r"(r2), "r"(r3) : "memory");
}
__device__ __forceinline__ void mma16816(float* d, uint32_t a0, uint32_t a1, uint32_t a2, uint32_t a3, uint32_t b0, uint32_t b1) {
    asm volatile("mma.sync.aligned.m16n8k16.row.col.f32.bf16.bf16.f32 {%0,%1,%2,%3}, {%4,%5,%6,%7}, {%8,%9}, {%0,%1,%2,%3};"
                 : "+f"(d[0]), "+f"(d[1]), "+f"(d[2]), "+f"(d[3]) : "r"(a0), "r"(a1), "r"(a2), "r"(a3), "r"(b0), "r"(b1));
}
__device__ __forceinline__ uint4 ld_relaxed4(const void* p) {
    uint4 v;
    asm volatile("ld.relaxed.gpu.global.v4.u32 {%0,%1,%2,%3}, [%4];" : "=r"(v.x), "=r"(v.y), "=r"(v.z), "=r"(v.w) : "l"(p) : "memory");
    return v;
}
__device__ __forceinline__ uint2 ld_relaxed2(const void* p) {
    uint2 v;
    asm volatile("ld.relaxed.gpu.global.v2.u32 {%0,%1}, [%2];" : "=r"(v.x), "=r"(v.y) : "l"(p) : "memory");
    return v;
}
__device__ __forceinline__ uint32_t ld_relaxed(const void* p) {
    uint32_t v;
    asm volatile("ld.relaxed.gpu.global.u32 %0, [%1];" : "=r"(v) : "l"(p) : "memory");
    return v;
}
__device__ __forceinline__ void st_relaxed4(void* p, uint32_t a, uint32_t b, uint32_t c, uint32_t d) {
    asm volatile("st.relaxed.gpu.global.v4.u32 [%0], {%1,%2,%3,%4};" ::"l"(p), "r"(a), "r"(b), "r"(c), "r"(d) : "memory");
}
__device__ __forceinline__ void st_relaxed(void* p, uint32_t a) {
    asm volatile("st.relaxed.gpu.global.u32 [%0], %1;" ::"l"(p), "r"(a) : "memory");
}
__device__ __forceinline__ void xchg_word(uint32_t* p, uint32_t v) {
    asm volatile("{\n.reg .b32 old;\natom.relaxed.gpu.global.exch.b32 old, [%0], %1;\n}" ::"l"(p), "r"(v) : "memory");
}
__device__ __forceinline__ void red_max(unsigned* p, unsigned v) {
    asm volatile("red.relaxed.gpu.global.max.u32 [%0], %1;" ::"l"(p), "r"(v) : "memory");
}
__device__ __forceinline__ void sts32(uint32_t a, uint32_t v) { asm volatile("st.shared.u32 [%0], %1;" ::"r"(a), "r"(v) : "memory"); }
__device__ __forceinline__ void sts16(uint32_t a, uint16_t v) { asm volatile("st.shared.u16 [%0], %1;" ::"r"(a), "h"(v) : "memory"); }
__device__ __forceinline__ void stsf(uint32_t a, float v) { asm volatile("st.shared.f32 [%0], %1;" ::"r"(a), "f"(v) : "memory"); }
__device__ __forceinline__ void sts128(uint32_t a, uint32_t x, uint32_t y, uint32_t z, uint32_t w) {
    asm volatile("st.shared.v4.u32 [%0], {%1,%2,%3,%4};" ::"r"(a), "r"(x), "r"(y), "r"(z), "r"(w) : "memory");
}
__device__ __forceinline__ uint4 lds128(uint32_t a) {
    uint4 v; asm volatile("ld.shared.v4.u32 {%0,%1,%2,%3}, [%4];" : "=r"(v.x), "=r"(v.y), "=r"(v.z), "=r"(v.w) : "r"(a) : "memory"); return v;
}
__device__ __forceinline__ float ldsf(uint32_t a) { float v; asm volatile("ld.shared.f32 %0, [%1];" : "=f"(v) : "r"(a) : "memory"); return v; }
__device__ __forceinline__ uint32_t lds32(uint32_t a) { uint32_t v; asm volatile("ld.shared.u32 %0, [%1];" : "=r"(v) : "r"(a) : "memory"); return v; }
__device__ __forceinline__ float2 ldsf2(uint32_t a) { float2 v; asm volatile("ld.shared.v2.f32 {%0,%1}, [%2];" : "=f"(v.x), "=f"(v.y) : "r"(a) : "memory"); return v; }
__device__ __forceinline__ unsigned gtime() { unsigned t; asm volatile("mov.u32 %0, %%globaltimer_lo;" : "=r"(t)::"memory"); return t; }
__device__ __forceinline__ float ex2(float x) { float y; asm("ex2.approx.ftz.f32 %0, %1;" : "=f"(y) : "f"(x)); return y; }

__device__ __forceinline__ uint32_t tagf(float v, uint32_t tag) { return (__float_as_uint(v) & ~3u) | 2u | tag; }
__device__ __forceinline__ float untag(uint32_t w) { return __uint_as_float(w & ~3u); }
__device__ __forceinline__ bool tags_ok(const uint4& v, uint32_t tag) {
    const uint32_t t = tag | 2u;
    return (((v.x ^ t) | (v.y ^ t) | (v.z ^ t) | (v.w ^ t)) & 3u) == 0;
}
__device__ __forceinline__ bool tags1_ok(const uint4& v, uint32_t tag) { const uint32_t t = tag << 16; return (((v.x ^ t) | (v.y ^ t) | (v.z ^ t) | (v.w ^ t)) & 0x10000u) == 0; }
__device__ __forceinline__ void delay_ns(unsigned ns) { const unsigned t0 = gtime(); while (gtime() - t0 < ns) { } }
__device__ __forceinline__ uint32_t pack_tagged(float lo, float hi, uint32_t tag) {
    uint32_t r0 = __float_as_uint(lo) + 0x8000u;
    uint32_t r1 = __float_as_uint(hi) + 0x10000u;
    return (__byte_perm(r0, r1, 0x7632) & ~0x10000u) | (tag << 16);
}
__device__ __forceinline__ uint32_t pack_bf16(float lo, float hi) {
    uint32_t r;
    asm("cvt.rn.bf16x2.f32 %0, %1, %2;" : "=r"(r) : "f"(hi), "f"(lo));
    return r;
}
__device__ __forceinline__ void pace_until(unsigned g0, uint32_t t16) {
    const unsigned t = t16 >> 4;
    while (gtime() - g0 < t) {
        __nanosleep(20);
    }
}
__device__ __forceinline__ void sts64(uint32_t a, uint32_t x, uint32_t y) { asm volatile("st.shared.v2.u32 [%0], {%1,%2};" ::"r"(a), "r"(x), "r"(y) : "memory"); }
__device__ __forceinline__ void hilo2(float v0, float v1, uint32_t& hi, uint32_t& lo) {
    asm("cvt.rn.bf16x2.f32 %0, %1, %2;" : "=r"(hi) : "f"(v1), "f"(v0));
    float r0 = v0 - __uint_as_float(hi << 16), r1 = v1 - __uint_as_float(hi & 0xffff0000u);
    asm("cvt.rn.bf16x2.f32 %0, %1, %2;" : "=r"(lo) : "f"(r1), "f"(r0));
}
__device__ __forceinline__ void sts_hilo(uint32_t a_hi, uint32_t lo_off, float v) {
    __nv_bfloat16 h = __float2bfloat16_rn(v);
    __nv_bfloat16 l = __float2bfloat16_rn(v - __bfloat162float(h));
    sts16(a_hi, __bfloat16_as_ushort(h));
    sts16(a_hi + lo_off, __bfloat16_as_ushort(l));
}
__device__ __forceinline__ float bf16lo(uint32_t w) { return __uint_as_float(w << 16); }
__device__ __forceinline__ float bf16hi(uint32_t w) { return __uint_as_float(w & 0xffff0000u); }
__device__ __forceinline__ float warp_sum(float v) {
#pragma unroll
    for (int o = 16; o; o >>= 1) v += __shfl_xor_sync(0xffffffffu, v, o);
    return v;
}
__device__ __forceinline__ float warp_max(float v) {
#pragma unroll
    for (int o = 16; o; o >>= 1) v = fmaxf(v, __shfl_xor_sync(0xffffffffu, v, o));
    return v;
}

__device__ __forceinline__ uint64_t make_desc(uint32_t addr, uint32_t lbo, uint32_t sbo) {
    return (uint64_t)((addr & 0x3FFFF) >> 4) | ((uint64_t)(lbo >> 4) << 16) | ((uint64_t)(sbo >> 4) << 32) | (1ull << 62);
}
__device__ __forceinline__ uint64_t desc_add(uint64_t d, uint32_t off) { return d + (uint64_t)(off >> 4); }
__device__ __forceinline__ void wg_fence() { asm volatile("wgmma.fence.sync.aligned;" ::: "memory"); }
__device__ __forceinline__ void wg_commit() { asm volatile("wgmma.commit_group.sync.aligned;" ::: "memory"); }
__device__ __forceinline__ void wg_wait0() { asm volatile("wgmma.wait_group.sync.aligned 0;" ::: "memory"); }
template <int TA>
__device__ __forceinline__ void wgmma_n32(float* d, uint64_t da, uint64_t db, int scale_d) {
    asm volatile("{\n.reg .pred p;\nsetp.ne.b32 p, %18, 0;\n"
                 "wgmma.mma_async.sync.aligned.m64n32k16.f32.bf16.bf16 "
                 "{%0,%1,%2,%3,%4,%5,%6,%7,%8,%9,%10,%11,%12,%13,%14,%15}, %16, %17, p, 1, 1, %19, 0;\n}"
                 : "+f"(d[0]), "+f"(d[1]), "+f"(d[2]), "+f"(d[3]), "+f"(d[4]), "+f"(d[5]), "+f"(d[6]), "+f"(d[7]),
                   "+f"(d[8]), "+f"(d[9]), "+f"(d[10]), "+f"(d[11]), "+f"(d[12]), "+f"(d[13]), "+f"(d[14]), "+f"(d[15])
                 : "l"(da), "l"(db), "r"(scale_d), "n"(TA));
}

__device__ __forceinline__ uint32_t bvec_addr(uint32_t base, uint32_t lo_off, uint32_t zero, int lane, int& kstep_bytes) {
    int n = lane & 7, kh = (lane >> 3) & 1;
    if (n < 2) { kstep_bytes = 32; return base + n * lo_off + kh * 16; }
    kstep_bytes = 0;
    return zero;
}

template <int NP>
__device__ __forceinline__ float cta_reduce32(const uint4* part, uint32_t red, uint32_t tag, int warp, int lane) {
    constexpr int NI = NP / 32;
    const uint4* src = part + (warp * (NP / 8) + (lane >> 3)) * 8 + (lane & 7);
    uint4 v[NI];
    int it = 0;
    uint32_t pend = (1u << NI) - 1u;
    while (true) {
#pragma unroll
        for (int k = 0; k < NI; k++) if (pend & (1u << k)) v[k] = ld_relaxed4(src + k * 32);
#pragma unroll
        for (int k = 0; k < NI; k++) if (tags_ok(v[k], tag)) pend &= ~(1u << k);
        if (__all_sync(0xffffffffu, pend == 0)) break;
        if (++it > SPIN_LIMIT) __trap();
    }
    float x0 = 0.f, x1 = 0.f, x2 = 0.f, x3 = 0.f;
#pragma unroll
    for (int k = 0; k < NI; k++) { x0 += untag(v[k].x); x1 += untag(v[k].y); x2 += untag(v[k].z); x3 += untag(v[k].w); }
    const bool b4 = lane & 16, b3 = lane & 8;
    const float t0 = (b4 ? x2 : x0) + __shfl_xor_sync(0xffffffffu, b4 ? x0 : x2, 16);
    const float t1 = (b4 ? x3 : x1) + __shfl_xor_sync(0xffffffffu, b4 ? x1 : x3, 16);
    const float s0 = (b3 ? t1 : t0) + __shfl_xor_sync(0xffffffffu, b3 ? t0 : t1, 8);
    stsf(red + (warp * 32 + 4 * (lane & 7) + 2 * (lane >> 4) + ((lane >> 3) & 1)) * 4, s0);
    nbar_sync(NB_CMP, 256);
    float t = 0.f;
#pragma unroll
    for (int w = 0; w < 8; w++) t += ldsf(red + (w * 32 + lane) * 4);
    return t;
}

template <int KSTEPS>
__device__ __forceinline__ void frag576_load(uint32_t (*af)[2][KSTEPS][4], uint32_t tile, int warp, int lane) {
    const int mi = lane >> 3, r8 = lane & 7;
    const uint32_t base = tile + (mi >> 1) * 9216 + (warp >> 1) * 1024 + r8 * 128;
    const int cc = (warp & 1) * 4 + (mi & 1);
    const uint32_t a0 = base + ((cc ^ r8) << 4), a1 = base + (((cc + 2) ^ r8) << 4);
#pragma unroll
    for (int pi = 0; pi < 3; pi++) {
        if (pi < 2 || warp < 2) {
#pragma unroll
            for (int s = 0; s < KSTEPS; s++) {
                ldsm4t(a0 + pi * 4096 + s * 18432, af[pi][0][s][0], af[pi][0][s][1], af[pi][0][s][2], af[pi][0][s][3]);
                ldsm4t(a1 + pi * 4096 + s * 18432, af[pi][1][s][0], af[pi][1][s][1], af[pi][1][s][2], af[pi][1][s][3]);
            }
        }
    }
}
template <int KSTEPS>
__device__ __forceinline__ void gemv576_finish(uint32_t (*af)[2][KSTEPS][4], uint32_t vec, uint32_t lo_off, uint32_t zero, uint4* part, int b,
                                               uint32_t tag, int warp, int lane) {
    int kb; uint32_t ba = bvec_addr(vec, lo_off, zero, lane, kb);
    uint32_t bf[KSTEPS][2];
#pragma unroll
    for (int s = 0; s < KSTEPS; s++) ldsm2(ba + s * kb, bf[s][0], bf[s][1]);
    float acc[3][2][4] = {};
#pragma unroll
    for (int s = 0; s < KSTEPS; s++)
#pragma unroll
        for (int pi = 0; pi < 3; pi++)
            if (pi < 2 || warp < 2) {
#pragma unroll
                for (int tl = 0; tl < 2; tl++)
                    mma16816(acc[pi][tl], af[pi][tl][s][0], af[pi][tl][s][1], af[pi][tl][s][2], af[pi][tl][s][3], bf[s][0], bf[s][1]);
            }
    const int src = lane & ~3, q = lane & 3;
    uint32_t* dst = (uint32_t*)part + (warp * 128 + b) * 32 + 8 * q + (lane >> 2);
#pragma unroll
    for (int pi = 0; pi < 3; pi++)
        if (pi < 2 || warp < 2) {
            const float v0 = __shfl_sync(0xffffffffu, acc[pi][0][0] + acc[pi][0][1], src), v1 = __shfl_sync(0xffffffffu, acc[pi][0][2] + acc[pi][0][3], src);
            const float v2 = __shfl_sync(0xffffffffu, acc[pi][1][0] + acc[pi][1][1], src), v3 = __shfl_sync(0xffffffffu, acc[pi][1][2] + acc[pi][1][3], src);
            xchg_word(dst + pi * (8 * 128 * 32), tagf(q == 0 ? v0 : q == 1 ? v1 : q == 2 ? v2 : v3, tag));
        }
}

__global__ void __cluster_dims__(2, 1, 1) __launch_bounds__(NTHREADS, 1)
fused_decode_kernel(const __grid_constant__ CUtensorMap tm_op, const __grid_constant__ CUtensorMap tm_st, const __grid_constant__ CUtensorMap tm_wuk, const __grid_constant__ CUtensorMap tm_ckv, const __grid_constant__ CUtensorMap tm_wuv,
                    const __grid_constant__ CUtensorMap tm_wo, const __grid_constant__ CUtensorMap tm_w1,
                    const __grid_constant__ CUtensorMap tm_w2, const Params prm)
{
    extern __shared__ uint8_t smem_raw[];
    const uint32_t sb = (smem_u32(smem_raw) + 1023u) & ~1023u;
    const int tid = threadIdx.x, warp = tid >> 5, lane = tid & 31;
    const int b = blockIdx.x;
    const uint32_t bars = sb + R_BAR;
    const uint32_t zero = sb + R_ZERO;
    auto BAR = [&](int i) { return bars + 8u * i; };

    const unsigned g0 = gtime();
    uint32_t xw[9];
    unsigned epoch = 0;
    auto init_barriers = [&]() {
        if (lane == 0) {
#pragma unroll
            for (int j = 0; j < 2; j++) {
                const int i = warp + 12 * j;
                if (i < NBAR) {
                    const uint32_t cnt = i == B_WQ ? 256u : (i == B_FREEC || i == B_FS) ? 8u : i == B_RQ ? 2u : 1u;
                    mbar_init(BAR(i), cnt);
                    const uint32_t tx = i == B_WUK ? 32768u : (i >= B_CKV0 && i <= B_CKV3) ? 16384u : i == B_WUV ? 32768u
                                      : i == B_WO ? ((b & 1) ? 32768u : 40960u) : (i == B_W1 || i == B_W2) ? 55296u
                                      : (i == B_XQ || i == B_XC) ? 512u : i == B_QA ? 32768u : (i == B_ST || i == B_SL) ? 128u : i == B_IN ? 16384u : 0u;
                    if (tx) mbar_expect_tx(BAR(i), tx);
                }
            }
            asm volatile("fence.mbarrier_init.release.cluster;" ::: "memory");
        }
    };
    const __nv_bfloat16* wq_src = prm.wq + (size_t)(32 * (b & 1) + (tid >> 3)) * 4096 + (b >> 1) * 64 + (tid & 7) * 8;
    const uint32_t wq_off = (tid >> 3) * 128 + (((tid & 7) ^ ((tid >> 3) & 7)) << 4);
    if (warp < 8) {
        cp_async16(sb + R_A + wq_off, wq_src);
        init_barriers();
        if (tid < 144) {
            if (b < NFFN) st_relaxed4(g_pE8 + ((tid >> 3) * 128 + b) * 8 + (tid & 7), 0, 0, 0, 0);
            if (tid < ((b & 1) ? 64 : 80)) st_relaxed4(g_pE6 + (((tid >> 3) + 10 * (b & 1)) * 64 + (b >> 1)) * 8 + (tid & 7), 0, 0, 0, 0);
        }
        else if (tid >= 160 && tid < 160 + 2 * FREP) st_relaxed4(g_flagB + (((tid - 160) >> 1) * 128 + b) * 2 + (tid & 1), 0, 0, 0, 0);
        else if (tid >= 192 && tid < 224) st_relaxed4(g_xq + b * 32 + (tid - 192), 0, 0, 0, 0);
#pragma unroll 1
        for (int i = 1; i < 9; i++) {
            pace_until(g0, START_NS * 16 + i * time16(4096, RATE_A, NCTA));
            cp_async16(sb + R_A + i * 4096 + wq_off, wq_src + (size_t)i * 64 * 4096);
        }
    } else if (warp == 9) {
        init_barriers();
        epoch = ld_relaxed(&g_epoch);
#pragma unroll
        for (int i = 0; i < 9; i++) xw[i] = __ldg((const uint32_t*)prm.x + lane + 32 * i);
        if (lane < 4) sts32(zero + 4 * lane, 0u);
    } else {
        init_barriers();
        if (warp == 8) {
            if (lane < 8) {
                const CUtensorMap* t = lane == 7 ? &tm_st : lane == 0 ? &tm_ckv : lane == 1 ? &tm_wuv : lane == 2 ? &tm_wo : lane == 3 ? &tm_w1 : lane == 4 ? &tm_w2 : lane == 5 ? &tm_wuk : &tm_op;
                prefetch_tmap(t);
            }
        } else {
            epoch = ld_relaxed(&g_epoch);
            if (b >= NFFN && b < NFFN + NRED && warp == 10)
                for (int r = lane >> 3; r < HREP; r += 4) st_relaxed4((uint32_t*)g_hbuf + r * 576 + 32 * (b - NFFN) + (lane & 7) * 4, 0, 0, 0, 0);
        }
    }
    if (warp == 9) {
        float sum = 0.f;
#pragma unroll
        for (int i = 0; i < 9; i++) sum += bf16lo(xw[i]) + bf16hi(xw[i]);
        const float ln_mean = warp_sum(sum) * (1.f / 576.f);
        float sq = 0.f;
#pragma unroll
        for (int i = 0; i < 9; i++) { float a = bf16lo(xw[i]) - ln_mean, c = bf16hi(xw[i]) - ln_mean; sq += a * a + c * c; }
        const float ln_rstd = rsqrtf(warp_sum(sq) * (1.f / 576.f) + 1e-5f);
#pragma unroll
        for (int i = 0; i < 9; i++) {
            const int m = 2 * (lane + 32 * i);
            const int e = 32 * (m >> 6) + (m & 31);
            if (((m >> 5) & 1) == (b & 1)) {
                uint32_t hi, lo;
                hilo2((bf16lo(xw[i]) - ln_mean) * ln_rstd, (bf16hi(xw[i]) - ln_mean) * ln_rstd, hi, lo);
                sts32(sb + R_VXN + e * 2, hi);
                sts32(sb + R_VXN + VXN_LO + e * 2, lo);
            }
        }
        if (lane == 0) { sts32(sb + R_TAG, (epoch + 1u) & 1u); sts32(sb + R_TAG + 4, epoch + 1u); }
    }
    nbar_sync(NB_INIT, NTHREADS);
    asm volatile("barrier.cluster.arrive.relaxed.aligned;" ::: "memory");

    if (warp < 8) {
        const int mi = lane >> 3, r8 = lane & 7, q4 = lane & 3, g8 = lane >> 2;
        cp_async_arrive(BAR(B_WQ));
        const uint32_t tag = lds32(sb + R_TAG);
        {
            const int mt = warp & 3, kh = warp >> 2;
            const uint32_t aa = sb + R_A + (144 * kh + (mi >> 1) * 8 + r8) * 128 + (((2 * mt + (mi & 1)) ^ r8) << 4);
            int kb; uint32_t ba = bvec_addr(sb + R_VXN + kh * 288, VXN_LO, zero, lane, kb);
            uint32_t bf[9][2];
#pragma unroll
            for (int s = 0; s < 9; s++) ldsm2(ba + s * kb, bf[s][0], bf[s][1]);
            mbar_wait(BAR(B_WQ));
            float acc[3][4] = {};
#pragma unroll
            for (int s = 0; s < 9; s++) {
                uint32_t a0, a1, a2, a3;
                ldsm4t(aa + s * 2048, a0, a1, a2, a3);
                mma16816(acc[s % 3], a0, a1, a2, a3, bf[s][0], bf[s][1]);
            }
            const float v0 = (acc[0][0] + acc[0][1]) + (acc[1][0] + acc[1][1]) + (acc[2][0] + acc[2][1]);
            const float v1 = (acc[0][2] + acc[0][3]) + (acc[1][2] + acc[1][3]) + (acc[2][2] + acc[2][3]);
            asm volatile("barrier.cluster.wait.acquire.aligned;" ::: "memory");
            const uint32_t xq = sb + R_XQP + (kh * 64 + mt * 16 + g8) * 4;
            if (q4 == 0) {
                const uint32_t rq = mapa(xq + 512, (b & 1) ^ 1), rb = mapa(BAR(B_XQ), (b & 1) ^ 1);
                st_async_f32(rq, v0, rb);
                st_async_f32(rq + 32, v1, rb);
                stsf(xq, v0); stsf(xq + 32, v1);
                uint32_t* dst = (uint32_t*)g_xq + b * 128 + kh * 64 + mt * 16 + g8;
                xchg_word(dst, tagf(v0, tag));
                xchg_word(dst + 8, tagf(v1, tag));
            }
        }
        {
            const int h = b >> 2;
            const int row = 16 * warp + (mi & 1) * 8 + r8;
            const uint32_t aa = sb + R_A + R_A_WUK + (row >> 5) * 8192 + (row & 31) * 128;
            uint32_t af[8][4];
            if (warp == 2) nbar_arrive(NB_CMP, 256); else nbar_sync(NB_CMP, 256);
            if (warp < 2) {
                mbar_wait_cluster(BAR(B_XQ));
                const uint32_t xq = sb + R_XQP + tid * 4;
                const float qv = (ldsf(xq) + ldsf(xq + 256)) + (ldsf(xq + 512) + ldsf(xq + 768));
                sts_hilo(sb + R_VQ + (64 * ((b >> 1) & 1) + tid) * 2, VQ_LO, qv);
            } else if (warp == 2) {
                const uint2* src = (const uint2*)(g_xq + ((b & ~3) + ((b & 2) ^ 2)) * 32) + lane;
                uint2 u[4]; int it = 0; uint32_t pend = 0xfu;
                while (true) {
#pragma unroll
                    for (int k = 0; k < 4; k++) if (pend & (1u << k)) u[k] = ld_relaxed2(src + 32 * k);
#pragma unroll
                    for (int k = 0; k < 4; k++) if ((((u[k].x ^ (tag | 2u)) | (u[k].y ^ (tag | 2u))) & 3u) == 0) pend &= ~(1u << k);
                    if (__all_sync(0xffffffffu, pend == 0)) break;
                    if (++it > SPIN_LIMIT) __trap();
                }
                uint2 v;
                v.x = __float_as_uint((untag(u[0].x) + untag(u[1].x)) + (untag(u[2].x) + untag(u[3].x)));
                v.y = __float_as_uint((untag(u[0].y) + untag(u[1].y)) + (untag(u[2].y) + untag(u[3].y)));
                uint32_t hi, lo;
                hilo2(__uint_as_float(v.x), __uint_as_float(v.y), hi, lo);
                const uint32_t a = sb + R_VQ + (64 * (((b >> 1) & 1) ^ 1) + 2 * lane) * 2;
                sts32(a, hi); sts32(a + VQ_LO, lo);
            }
            mbar_wait(BAR(B_WUK));
#pragma unroll
            for (int s = 0; s < 8; s++) {
                const int cc = (s & 3) * 2 + (mi >> 1);
                ldsm4(aa + (s >> 2) * 4096 + ((cc ^ r8) << 4), af[s][0], af[s][1], af[s][2], af[s][3]);
            }
            nbar_sync(NB_VEC, 256);
            int kb; uint32_t ba = bvec_addr(sb + R_VQ, VQ_LO, zero, lane, kb);
            float acc[2][4] = {};
#pragma unroll
            for (int s = 0; s < 8; s++) {
                uint32_t b0, b1;
                ldsm2(ba + s * kb, b0, b1);
                mma16816(acc[s & 1], af[s][0], af[s][1], af[s][2], af[s][3], b0, b1);
            }
            const float sc = 0.08838834764831845f * 1.4426950408889634f;
            const float v0 = ((acc[0][0] + acc[0][1]) + (acc[1][0] + acc[1][1])) * sc;
            const float v1 = ((acc[0][2] + acc[0][3]) + (acc[1][2] + acc[1][3])) * sc;
            if (q4 == 0) {
                const uint32_t st = sb + R_RED + (warp >> 2) * 128 + g8 * 2;
                const int c0 = ((warp & 3) * 2) ^ (h & 7), c1 = c0 ^ 1;
                uint32_t w0 = __bfloat16_as_ushort(__float2bfloat16_rn(v0)), w1 = __bfloat16_as_ushort(__float2bfloat16_rn(v1));
                if (g8 == 0) {
                    if ((c0 & 1) == 0) w0 = (((__float_as_uint(v0) + 0x10000u) >> 16) & 0xfffeu) | tag;
                    else w1 = (((__float_as_uint(v1) + 0x10000u) >> 16) & 0xfffeu) | tag;
                }
                sts16(st + (c0 << 4), (uint16_t)w0);
                sts16(st + (c1 << 4), (uint16_t)w1);
            }
            fence_async_smem();
        }
        nbar_sync(NB_CMP, 256);
        const uint32_t fval = lds32(sb + R_TAG + 4);
        if (warp == 0 && (lane == 0 || lane == 8)) {
            mbar_wait(BAR(B_RQ));
            char* dst = (char*)g_qabs + (2 * (b & 3) + (lane >> 3)) * 4096 + (b >> 2) * 128;
            asm volatile("cp.async.bulk.global.shared::cta.bulk_group [%0], [%1], 128;" ::"l"(dst), "r"(sb + R_RED + lane * 16) : "memory");
            asm volatile("cp.async.bulk.commit_group;" ::: "memory");
        }
        if (tid == 0) {
            delay_ns(QABS_WAIT_NS);
            const uint32_t half = (b & 1) * 16384;
            asm volatile("cp.async.bulk.shared::cluster.global.mbarrier::complete_tx::bytes.multicast::cluster [%0], [%1], 16384, [%2], %3;"
                         ::"r"(sb + R_A + half), "l"((const char*)g_qabs + half), "r"(BAR(B_QA)), "h"((uint16_t)3) : "memory");
        }
        mbar_wait(BAR(B_QA));
        if (warp == 0 && (lane == 0 || lane == 8)) asm volatile("cp.async.bulk.wait_group.read 0;" ::: "memory");
        {
#pragma unroll
            for (int i = 0; i < 4; i++) {
                const uint32_t off = (tid + 256 * i) * 32;
                uint32_t w = lds32(sb + R_A + off);
                if ((w & 1u) != tag) {
                    int it = 0;
                    uint4 x, y;
                    do { x = ld_relaxed4((const char*)g_qabs + off); y = ld_relaxed4((const char*)g_qabs + off + 16); if (++it > SPIN_LIMIT) __trap(); } while ((x.x & 1u) != tag);
                    sts128(sb + R_A + off, x.x, x.y, x.z, x.w); sts128(sb + R_A + off + 16, y.x, y.y, y.z, y.w);
                    w = x.x;
                }
                sts32(sb + R_A + off, w & ~1u);
            }
        }
        fence_async_smem();
        nbar_sync(NB_CMP, 256);
        float mx[8];
        if (warp < 4) {
            float s4[4][16];
#pragma unroll
            for (int a = 0; a < 4; a++)
#pragma unroll
                for (int i = 0; i < 16; i++) s4[a][i] = 0.f;
            const uint64_t da0 = make_desc(sb + R_C, 16, 1024), db0 = make_desc(sb + R_A, 16, 1024);
#pragma unroll
            for (int k = 0; k < 4; k++) {
                mbar_wait(BAR(B_CKV0 + k));
                wg_fence();
#pragma unroll
                for (int u = 0; u < 8; u++) {
                    const int blk = 2 * k + (u >> 2), ks = u & 3;
                    wgmma_n32<0>(s4[ks], desc_add(da0, blk * 8192 + ks * 32), desc_add(db0, blk * 4096 + ks * 32), (k | (u >> 2)) != 0);
                }
                wg_commit();
            }
            wg_wait0();
            float s[16];
#pragma unroll
            for (int i = 0; i < 16; i++) s[i] = (s4[0][i] + s4[1][i]) + (s4[2][i] + s4[3][i]);
#pragma unroll
            for (int i = 0; i < 4; i++) {
                mx[2 * i] = fmaxf(s[4 * i], s[4 * i + 2]);
                mx[2 * i + 1] = fmaxf(s[4 * i + 1], s[4 * i + 3]);
            }
#pragma unroll
            for (int o = 4; o <= 16; o <<= 1)
#pragma unroll
                for (int i = 0; i < 8; i++) mx[i] = fmaxf(mx[i], __shfl_xor_sync(0xffffffffu, mx[i], o));
            if (g8 == 0) {
#pragma unroll
                for (int i = 0; i < 4; i++) {
                    stsf(sb + R_SMAX + (warp * 32 + 8 * i + 2 * q4) * 4, mx[2 * i]);
                    stsf(sb + R_SMAX + (warp * 32 + 8 * i + 2 * q4 + 1) * 4, mx[2 * i + 1]);
                }
            }
            nbar_sync(NB_WG0, 128);
#pragma unroll
            for (int i = 0; i < 4; i++) {
                float2 m0 = ldsf2(sb + R_SMAX + (0 * 32 + 8 * i + 2 * q4) * 4), m1 = ldsf2(sb + R_SMAX + (1 * 32 + 8 * i + 2 * q4) * 4);
                float2 m2 = ldsf2(sb + R_SMAX + (2 * 32 + 8 * i + 2 * q4) * 4), m3 = ldsf2(sb + R_SMAX + (3 * 32 + 8 * i + 2 * q4) * 4);
                mx[2 * i] = fmaxf(fmaxf(m0.x, m1.x), fmaxf(m2.x, m3.x));
                mx[2 * i + 1] = fmaxf(fmaxf(m0.y, m1.y), fmaxf(m2.y, m3.y));
            }
            if (warp == 0 && g8 == 0) {
                const uint32_t peer = (b & 1) ^ 1, rb = mapa(BAR(B_ST), peer);
#pragma unroll
                for (int i = 0; i < 8; i++) {
                    const uint32_t a = sb + R_ST + (8 * (i >> 1) + 2 * q4 + (i & 1)) * 4;
                    stsf(a, mx[i]);
                    st_async_f32(mapa(a + 256, peer), mx[i], rb);
                }
            }
            uint32_t pk[8];
#pragma unroll
            for (int i = 0; i < 4; i++) {
                uint32_t w0 = pack_bf16(ex2(s[4 * i] - mx[2 * i]), ex2(s[4 * i + 1] - mx[2 * i + 1]));
                uint32_t w1 = pack_bf16(ex2(s[4 * i + 2] - mx[2 * i]), ex2(s[4 * i + 3] - mx[2 * i + 1]));
                pk[i] = w0; pk[4 + i] = w1;
            }
            const int head = lane;
            uint32_t a = sb + R_P + head * 128;
            stsm4t(a + (((2 * warp) ^ (head & 7)) << 4), pk[0], pk[1], pk[2], pk[3]);
            stsm4t(a + (((2 * warp + 1) ^ (head & 7)) << 4), pk[4], pk[5], pk[6], pk[7]);
            fence_async_smem();
            nbar_arrive(NB_P, 160);
        }
        nbar_sync(NB_CMP, 256);
        {
            const int wg = __shfl_sync(0xffffffffu, warp >> 2, 0), w = warp & 3;
            const int rk = b & 1;
            const uint64_t db0 = make_desc(sb + R_P, 16, 1024);
            const uint64_t das = make_desc(sb + R_C + (4 * (rk ^ 1) + 2 * wg) * 8192, 1024, 1024);
            const uint64_t dak = make_desc(sb + R_C + (4 * rk + 2 * wg) * 8192, 1024, 1024);
            float os[2][16], ok_[2][16];
            wg_fence();
#pragma unroll
            for (int ks = 0; ks < 4; ks++)
#pragma unroll
                for (int t = 0; t < 2; t++) wgmma_n32<1>(os[t], desc_add(das, t * 8192 + ks * 2048), desc_add(db0, ks * 32), ks != 0);
            wg_commit();
#pragma unroll
            for (int ks = 0; ks < 4; ks++)
#pragma unroll
                for (int t = 0; t < 2; t++) wgmma_n32<1>(ok_[t], desc_add(dak, t * 8192 + ks * 2048), desc_add(db0, ks * 32), ks != 0);
            wg_commit();
            mbar_wait_cluster(BAR(B_ST));
            float f[8];
#pragma unroll
            for (int i = 0; i < 4; i++) {
                const float2 mo = ldsf2(sb + R_ST + (8 * i + 2 * q4) * 4), mp = ldsf2(sb + R_ST + 256 + (8 * i + 2 * q4) * 4);
                f[2 * i] = ex2(mo.x - fmaxf(mo.x, mp.x)); f[2 * i + 1] = ex2(mo.y - fmaxf(mo.y, mp.y));
            }
            asm volatile("wgmma.wait_group.sync.aligned 1;" ::: "memory");
            {
                const uint32_t peer = rk ^ 1, dst = mapa(sb + R_INBOX + tid * 16, peer), rb = mapa(BAR(B_IN), peer);
#pragma unroll
                for (int t = 0; t < 2; t++)
#pragma unroll
                    for (int ih = 0; ih < 2; ih++) {
                        uint32_t wd[4];
#pragma unroll
                        for (int k = 0; k < 4; k++) {
                            const int i = 2 * ih + (k >> 1), e = k & 1;
                            wd[k] = pack_bf16(os[t][4 * i + e] * f[2 * i + e], os[t][4 * i + 2 + e] * f[2 * i + e]);
                        }
                        st_async_v4(dst + (2 * t + ih) * 4096, wd[0], wd[1], wd[2], wd[3], rb);
                    }
            }
            wg_wait0();
            if (lane == 0) mbar_arrive(BAR(B_FREEC));
            mbar_wait_cluster(BAR(B_IN));
#pragma unroll
            for (int t = 0; t < 2; t++)
#pragma unroll
                for (int ih = 0; ih < 2; ih++) {
                    const uint4 pv = lds128(sb + R_INBOX + (2 * t + ih) * 4096 + tid * 16);
                    const uint32_t wd[4] = {pv.x, pv.y, pv.z, pv.w};
#pragma unroll
                    for (int k = 0; k < 4; k++) {
                        const int i = 2 * ih + (k >> 1), e = k & 1;
                        sts32(sb + R_A + (8 * i + 2 * q4 + e) * 512 + ((2 * wg + t) * 32 + ((w + q4) & 3) * 8 + g8) * 4,
                              pack_tagged(fmaf(ok_[t][4 * i + e], f[2 * i + e], bf16lo(wd[k])), fmaf(ok_[t][4 * i + 2 + e], f[2 * i + e], bf16hi(wd[k])), tag));
                    }
                }
            fence_async_smem();
            nbar_arrive(NB_G3, 320);
            mbar_wait(BAR(B_WUV));
        }
        nbar_arrive(NB_G1, 288);
        uint32_t cf[8][4];
        {
            const int h = b >> 2;
            {
                const uint32_t aa = sb + R_V + (128 * (warp >> 2) + (mi >> 1) * 8 + r8) * 128 + (((2 * (warp & 3) + (mi & 1)) ^ r8) << 4);
#pragma unroll
                for (int s = 0; s < 8; s++) ldsm4t(aa + s * 2048, cf[s][0], cf[s][1], cf[s][2], cf[s][3]);
            }
            uint4 v[8];
            {
                delay_ns(FLAG_WAIT_NS);
                bool ok = lane >= 8;
                const uint32_t* fl = (const uint32_t*)(g_flagB + ((b & (FREP - 1)) * 128 + 2 * (warp * 8 + (lane & 7)) + (b & 1)) * 2);
                int it = 0;
                while (true) {
                    if (!ok) ok = ld_relaxed(fl) == fval;
                    if (__all_sync(0xffffffffu, ok)) break;
                    if (++it > SPIN_LIMIT) __trap();
                }
            }
            if (lane == 0) mbar_arrive(BAR(B_FS));
            {
                const uint4* src = g_opart + ((size_t)(2 * h + (b & 1)) * 64 + warp * 8) * 32 + lane;
                int it = 0;
                while (true) {
#pragma unroll
                    for (int r = 0; r < 8; r++) v[r] = ld_relaxed4(src + r * 32);
                    bool ok = true;
#pragma unroll
                    for (int r = 0; r < 8; r++) ok = ok && tags1_ok(v[r], tag);
                    if (__all_sync(0xffffffffu, ok)) break;
                    if (++it > SPIN_LIMIT) __trap();
                }
            }
            nbar_sync(NB_VEC, 288);
            float acc[8] = {};
#pragma unroll
            for (int r = 0; r < 8; r++) {
                const float wt = ldsf(sb + R_WTS + (warp * 8 + r) * 4);
                acc[0] = fmaf(wt, bf16lo(v[r].x), acc[0]); acc[1] = fmaf(wt, __uint_as_float(v[r].x & 0xfffe0000u), acc[1]);
                acc[2] = fmaf(wt, bf16lo(v[r].y), acc[2]); acc[3] = fmaf(wt, __uint_as_float(v[r].y & 0xfffe0000u), acc[3]);
                acc[4] = fmaf(wt, bf16lo(v[r].z), acc[4]); acc[5] = fmaf(wt, __uint_as_float(v[r].z & 0xfffe0000u), acc[5]);
                acc[6] = fmaf(wt, bf16lo(v[r].w), acc[6]); acc[7] = fmaf(wt, __uint_as_float(v[r].w & 0xfffe0000u), acc[7]);
            }
            {
                const uint32_t a = sb + R_P + warp * 1024 + lane * 16;
                sts128(a, __float_as_uint(acc[0]), __float_as_uint(acc[1]), __float_as_uint(acc[2]), __float_as_uint(acc[3]));
                sts128(a + 512, __float_as_uint(acc[4]), __float_as_uint(acc[5]), __float_as_uint(acc[6]), __float_as_uint(acc[7]));
            }
            const int u_ = (tid >> 2) & 31, k_ = 4 * (tid >> 7) + (tid & 3), pos = 4 * u_ + (k_ >> 1);
            const uint32_t vo = sb + R_VO + (64 * (pos >> 5) + 16 * ((((pos >> 3) & 3) - (h >> 1)) & 3) + (pos & 7) + 8 * (k_ & 1)) * 2;
            nbar_sync(NB_CMP, 256);
            {
                float s0 = 0.f, s1 = 0.f;
#pragma unroll
                for (int w = 0; w < 8; w += 2) { s0 += ldsf(sb + R_P + w * 1024 + tid * 4); s1 += ldsf(sb + R_P + (w + 1) * 1024 + tid * 4); }
                sts_hilo(vo, VO_LO, s0 + s1);
            }
            nbar_sync(NB_CMP, 256);
        }
        {
            int kb; uint32_t ba = bvec_addr(sb + R_VO + (warp >> 2) * 256, VO_LO, zero, lane, kb);
            float acc[2][4] = {};
#pragma unroll
            for (int s = 0; s < 8; s++) {
                uint32_t b0, b1;
                ldsm2(ba + s * kb, b0, b1);
                mma16816(acc[s & 1], cf[s][0], cf[s][1], cf[s][2], cf[s][3], b0, b1);
            }
            if (q4 == 0) {
                const float v0 = (acc[0][0] + acc[0][1]) + (acc[1][0] + acc[1][1]), v1 = (acc[0][2] + acc[0][3]) + (acc[1][2] + acc[1][3]);
                const uint32_t xq = sb + R_XQP + ((warp >> 2) * 64 + (warp & 3) * 16 + g8) * 4;
                const uint32_t rq = mapa(xq + 512, (b & 1) ^ 1), rb = mapa(BAR(B_XC), (b & 1) ^ 1);
                st_async_f32(rq, v0, rb);
                st_async_f32(rq + 32, v1, rb);
                stsf(xq, v0); stsf(xq + 32, v1);
            }
        }
        {
            uint32_t af[2][2][4][4];
            const bool two = (b & 1) == 0 && warp < 2;
            mbar_wait(BAR(B_WO));
            {
                const uint32_t base = sb + R_O + (warp >> 1) * 8192 + ((mi >> 1) * 8 + r8) * 128;
                const int cc = (warp & 1) * 4 + (mi & 1);
                const uint32_t a0 = base + ((cc ^ r8) << 4), a1 = base + (((cc + 2) ^ r8) << 4);
#pragma unroll
                for (int pi = 0; pi < 2; pi++)
                    if (pi == 0 || two) {
#pragma unroll
                        for (int s = 0; s < 4; s++) {
                            ldsm4t(a0 + pi * 32768 + s * 2048, af[pi][0][s][0], af[pi][0][s][1], af[pi][0][s][2], af[pi][0][s][3]);
                            ldsm4t(a1 + pi * 32768 + s * 2048, af[pi][1][s][0], af[pi][1][s][1], af[pi][1][s][2], af[pi][1][s][3]);
                        }
                    }
            }
            nbar_sync(NB_CMP, 256);
            mbar_wait_cluster(BAR(B_XC));
            if (tid < 64) {
                const uint32_t xq = sb + R_XQP + tid * 4;
                sts_hilo(sb + R_VC + tid * 2, VC_LO, (ldsf(xq) + ldsf(xq + 256)) + (ldsf(xq + 512) + ldsf(xq + 768)));
            }
            nbar_sync(NB_CMP, 256);
            int kb; uint32_t ba = bvec_addr(sb + R_VC, VC_LO, zero, lane, kb);
            float acc[2][2][4] = {};
#pragma unroll
            for (int s = 0; s < 4; s++) {
                uint32_t b0, b1;
                ldsm2(ba + s * kb, b0, b1);
#pragma unroll
                for (int pi = 0; pi < 2; pi++)
                    if (pi == 0 || two) {
                        mma16816(acc[pi][0], af[pi][0][s][0], af[pi][0][s][1], af[pi][0][s][2], af[pi][0][s][3], b0, b1);
                        mma16816(acc[pi][1], af[pi][1][s][0], af[pi][1][s][1], af[pi][1][s][2], af[pi][1][s][3], b0, b1);
                    }
            }
            const int src = lane & ~3;
            uint32_t* dst = (uint32_t*)g_pE6 + ((10 * (b & 1) + warp) * 64 + (b >> 1)) * 32 + 8 * q4 + g8;
#pragma unroll
            for (int pi = 0; pi < 2; pi++)
                if (pi == 0 || two) {
                    const float v0 = __shfl_sync(0xffffffffu, acc[pi][0][0] + acc[pi][0][1], src), v1 = __shfl_sync(0xffffffffu, acc[pi][0][2] + acc[pi][0][3], src);
                    const float v2 = __shfl_sync(0xffffffffu, acc[pi][1][0] + acc[pi][1][1], src), v3 = __shfl_sync(0xffffffffu, acc[pi][1][2] + acc[pi][1][3], src);
                    xchg_word(dst + pi * (8 * 64 * 32), tagf(q4 == 0 ? v0 : q4 == 1 ? v1 : q4 == 2 ? v2 : v3, tag));
                }
        }
        if (b < NFFN) nbar_arrive(NB_G1, 288);
        if (b >= NFFN && b < NFFN + NRED) {
            const int p = b - NFFN;
            const float xres = __bfloat162float(prm.x[32 * p + lane]);
            const float hcol = xres + cta_reduce32<64>(g_pE6 + p * 512, sb + R_RED, tag, warp, lane);
            if (warp < HREP) xchg_word((uint32_t*)g_hbuf + warp * 576 + 32 * p + lane, tagf(hcol, tag));
            delay_ns(FFN_WAIT_NS);
            const float f = cta_reduce32<NFFN>(g_pE8 + p * 1024, sb + R_RED + 1024, tag, warp, lane);
            if (warp == 0) {
                prm.out[32 * p + lane] = __float2bfloat16_rn(hcol + f);
                if (p == 0 && lane == 0) st_relaxed(&g_epoch, lds32(sb + R_TAG + 4));
            }
        }
        if (b < NFFN) {
            uint32_t gf[3][2][3][4];
            float colsum = 0.f;
            {
                const uint32_t aa = sb + R_A + ((mi >> 1) * 8 + r8) * 96 + (mi & 1) * 16 + warp * 1536;
                uint32_t af[5][3][4];
                mbar_wait(BAR(B_W1));
#pragma unroll
                for (int k = 0; k < 5; k++) {
                    if (k < 4 || warp < 4) {
#pragma unroll
                        for (int mt = 0; mt < 3; mt++) ldsm4t(aa + k * 12288 + mt * 32, af[k][mt][0], af[k][mt][1], af[k][mt][2], af[k][mt][3]);
                    }
                }
                {
                    const uint32_t one = (lane >> 2) == 0 ? 0x3f803f80u : 0u;
                    float cs[3][4] = {};
#pragma unroll
                    for (int k = 0; k < 5; k++)
                        if (k < 4 || warp < 4) {
#pragma unroll
                            for (int mt = 0; mt < 3; mt++) mma16816(cs[mt], af[k][mt][0], af[k][mt][1], af[k][mt][2], af[k][mt][3], one, one);
                        }
                    if (q4 == 0) {
#pragma unroll
                        for (int mt = 0; mt < 3; mt++) {
                            stsf(sb + R_RED + 2048 + (warp * 48 + mt * 16 + g8) * 4, cs[mt][0]);
                            stsf(sb + R_RED + 2048 + (warp * 48 + mt * 16 + g8 + 8) * 4, cs[mt][2]);
                        }
                    }
                }
                nbar_sync(NB_CMP, 256);
                if (tid >= 208) {
#pragma unroll
                    for (int w = 0; w < 8; w++) colsum += ldsf(sb + R_RED + 2048 + (w * 48 + tid - 208) * 4);
                }
                float acc[2][3][4] = {};
                int kb; uint32_t ba = bvec_addr(sb + R_VH, VH_LO, zero, lane, kb);
                ba += warp * kb;
                nbar_sync(NB_VEC, 288);
#pragma unroll
                for (int k = 0; k < 5; k++) {
                    if (k < 4 || warp < 4) {
                        uint32_t b0, b1;
                        ldsm2(ba + k * 8 * kb, b0, b1);
#pragma unroll
                        for (int mt = 0; mt < 3; mt++) mma16816(acc[k & 1][mt], af[k][mt][0], af[k][mt][1], af[k][mt][2], af[k][mt][3], b0, b1);
                    }
                }
                if (q4 == 0) {
#pragma unroll
                    for (int mt = 0; mt < 3; mt++) {
                        stsf(sb + R_RED + 512 + (warp * 48 + mt * 16 + g8) * 4, (acc[0][mt][0] + acc[0][mt][1]) + (acc[1][mt][0] + acc[1][mt][1]));
                        stsf(sb + R_RED + 512 + (warp * 48 + mt * 16 + g8 + 8) * 4, (acc[0][mt][2] + acc[0][mt][3]) + (acc[1][mt][2] + acc[1][mt][3]));
                    }
                }
            }
            nbar_sync(NB_CMP, 256);
            if (warp >= 6) {
                const int i = tid - 208;
                float a = 0.f;
                if (i >= 0) {
#pragma unroll
                    for (int w = 0; w < 8; w++) a += ldsf(sb + R_RED + 512 + (w * 48 + i) * 4);
                }
                nbar_sync(NB_G2, 96);
                if (i >= 0) {
                    const float2 mr = ldsf2(sb + R_WTS + 256);
                    a = mr.y * fmaf(-mr.x, colsum, a);
                    sts_hilo(sb + R_VU + i * 2, VU_LO, __fdividef(a, 1.f + __expf(-a)));
                }
            }
            mbar_wait(BAR(B_W2));
            frag576_load<3>(gf, sb + R_C, warp, lane);
            nbar_sync(NB_CMP, 256);
            gemv576_finish<3>(gf, sb + R_VU, VU_LO, zero, g_pE8, b, tag, warp, lane);
        }
    } else if (warp == 8) {
        if (lane == 0) {
            const uint64_t pol = policy_evict_first();
            uint32_t t16 = START_NS * 16 + 9 * time16(4096, RATE_A, NCTA);
#pragma unroll 1
            for (int k = 0; k < 4; k++) { pace_until(g0, t16); tma3(sb + R_A + R_A_WUK + k * 8192, &tm_wuk, 0, 128 * (b & 3) + 32 * k, 2 * (b >> 2), BAR(B_WUK), pol); t16 += time16(8192, RATE_A, NCTA); }
#pragma unroll 1
            for (int k = 0; k < 8; k++) { pace_until(g0, t16); tma3(sb + R_C + k * 8192, &tm_ckv, 0, 64 * b, k, BAR(B_CKV0 + (k >> 1)), pol); t16 += time16(8192, RATE_B, NCTA); }
#pragma unroll 1
            for (int k = 0; k < 4; k++) { pace_until(g0, t16); tma3(sb + R_V + k * 8192, &tm_wuv, 0, 256 * (b & 1) + 64 * k, b >> 1, BAR(B_WUV), pol); t16 += time16(8192, RATE_C, NCTA); }
#pragma unroll 1
            for (int k = 0; k < 5 - (b & 1); k++) {
                pace_until(g0, t16);
                tma3(sb + R_O + k * 8192, &tm_wo, 0, 64 * (b >> 1), 5 * (b & 1) + k, BAR(B_WO), pol);
                t16 += (b & 1) ? time16(9216, RATE_C, NCTA) : time16(36864 / 5, RATE_C, NCTA);
            }
#pragma unroll 1
            for (int k = 0; k < 9; k++) { pace_until(g0, t16); l2_prefetch(prm.w1 + (size_t)(k * 128 + b) * 4608, 4608); t16 += time16(4608, RATE_C, NCTA); }
#pragma unroll 1
            for (int k = 0; k < 9; k++) { pace_until(g0, t16); l2_prefetch(prm.w2 + (size_t)(k * 128 + b) * 4608, 4608); t16 += time16(4608, RATE_C, NCTA); }
        }
    } else if (warp == 9) {
        const uint32_t tag = (epoch + 1u) & 1u;
        {
            const int h = b >> 2;
            const uint32_t fval = epoch + 1u;
            nbar_sync(NB_G1, 288);
            delay_ns(FLAG_WAIT_NS);
            const uint32_t* fl = (const uint32_t*)(g_flagB + ((b & (FREP - 1)) * 128 + 2 * lane + ((h >> 2) & 1)) * 2);
            bool ok0 = false, ok1 = false;
            int it = 0;
            while (true) {
                if (!ok0) ok0 = ld_relaxed(fl) == fval;
                if (!ok1) ok1 = ld_relaxed(fl + 64 * 8) == fval;
                if (__all_sync(0xffffffffu, ok0 && ok1)) break;
                if (++it > SPIN_LIMIT) __trap();
            }
            const uint2* ssrc = (const uint2*)g_stats + ((h >> 2) * 64 + lane) * 4 + (h & 3);
            uint2 s0, s1;
            it = 0;
            while (true) {
                s0 = ld_relaxed2(ssrc); s1 = ld_relaxed2(ssrc + 32 * 4);
                const uint32_t t = tag | 2u;
                if (__all_sync(0xffffffffu, (((s0.x ^ t) | (s0.y ^ t) | (s1.x ^ t) | (s1.y ^ t)) & 3u) == 0)) break;
                if (++it > SPIN_LIMIT) __trap();
            }
            const float M = warp_max(fmaxf(untag(s0.x), untag(s1.x)));
            const float w0 = ex2(untag(s0.x) - M), w1 = ex2(untag(s1.x) - M);
            const float inv = __fdividef(1.f, warp_sum(fmaf(w0, untag(s0.y), w1 * untag(s1.y))));
            stsf(sb + R_WTS + lane * 4, w0 * inv);
            stsf(sb + R_WTS + (32 + lane) * 4, w1 * inv);
            nbar_arrive(NB_VEC, 288);
        }
        if (b < NFFN) {
            nbar_sync(NB_G1, 288);
            const uint4* src = g_hbuf + (b & (HREP - 1)) * 144;
            uint4 v[5];
            int it = 0;
            uint32_t pend = lane < 16 ? 0x1fu : 0xfu;
            while (true) {
#pragma unroll
                for (int k = 0; k < 5; k++) if (pend & (1u << k)) v[k] = ld_relaxed4(src + 32 * k + lane);
#pragma unroll
                for (int k = 0; k < 5; k++) if ((pend & (1u << k)) && tags_ok(v[k], tag)) pend &= ~(1u << k);
                if (__all_sync(0xffffffffu, pend == 0)) break;
                if (++it > SPIN_LIMIT) __trap();
            }
#pragma unroll
            for (int k = 0; k < 5; k++) {
                if (k < 4 || lane < 16) {
                    uint32_t h0, l0, h1, l1;
                    hilo2(untag(v[k].x), untag(v[k].y), h0, l0);
                    hilo2(untag(v[k].z), untag(v[k].w), h1, l1);
                    sts64(sb + R_VH + (32 * k + lane) * 8, h0, h1);
                    sts64(sb + R_VH + VH_LO + (32 * k + lane) * 8, l0, l1);
                }
            }
            nbar_arrive(NB_VEC, 288);
            const float pivot = __shfl_sync(0xffffffffu, untag(v[0].x), 0);
            float sum = 0.f, sq = 0.f;
#pragma unroll
            for (int k = 0; k < 5; k++) {
                if (k < 4 || lane < 16) {
                    const float d0 = untag(v[k].x) - pivot, d1 = untag(v[k].y) - pivot, d2 = untag(v[k].z) - pivot, d3 = untag(v[k].w) - pivot;
                    sum += (d0 + d1) + (d2 + d3);
                    sq = fmaf(d0, d0, fmaf(d1, d1, fmaf(d2, d2, fmaf(d3, d3, sq))));
                }
            }
#pragma unroll
            for (int o = 16; o; o >>= 1) { sum += __shfl_xor_sync(0xffffffffu, sum, o); sq += __shfl_xor_sync(0xffffffffu, sq, o); }
            const float dm = sum * (1.f / 576.f);
            if (lane == 0) sts64(sb + R_WTS + 256, __float_as_uint(pivot + dm), __float_as_uint(rsqrtf(fmaxf(sq * (1.f / 576.f) - dm * dm, 0.f) + 1e-5f)));
            nbar_arrive(NB_G2, 96);
        }
    } else {
        if (warp == 11) {
            if (lane < 16) sts128(sb + R_STST + lane * 16, epoch & 1u, 0, 0, 0);
            fence_async_smem();
            __syncwarp();
            if (lane == 0 || lane == 8) {
                char* dst = (char*)g_qabs + (2 * (b & 3) + (lane >> 3)) * 4096 + (b >> 2) * 128;
                asm volatile("cp.async.bulk.global.shared::cta.bulk_group [%0], [%1], 128;" ::"l"(dst), "r"(sb + R_STST + lane * 16) : "memory");
                asm volatile("cp.async.bulk.commit_group;" ::: "memory");
                asm volatile("cp.async.bulk.wait_group 0;" ::: "memory");
                mbar_arrive(BAR(B_RQ));
            }
            __syncwarp();
            nbar_sync(NB_G3, 320);
            if (lane == 0) {
                asm volatile("cp.async.bulk.tensor.4d.global.shared::cta.tile.bulk_group [%0, {%1, %2, %3, %4}], [%5];"
                             ::"l"(&tm_st), "r"(0), "r"(b >> 1), "r"(b & 1), "r"(0), "r"(sb + R_STST) : "memory");
                asm volatile("cp.async.bulk.tensor.4d.global.shared::cta.tile.bulk_group [%0, {%1, %2, %3, %4}], [%5];"
                             ::"l"(&tm_op), "r"(0), "r"(b >> 1), "r"(b & 1), "r"(0), "r"(sb + R_A) : "memory");
                asm volatile("cp.async.bulk.commit_group;" ::: "memory");
            }
            __syncwarp();
            if (lane < FREP) red_max((unsigned*)(g_flagB + (lane * 128 + b) * 2), epoch + 1u);
            if (lane == 0) {
                asm volatile("cp.async.bulk.wait_group.read 0;" ::: "memory");
                if (b < NFFN) {
                    mbar_wait(BAR(B_FREEC));
                    mbar_wait(BAR(B_FS));
                    delay_ns(LATE_WAIT_NS);
                    const unsigned g1 = gtime();
                    const uint64_t pol = policy_evict_first();
                    uint32_t t16 = 0;
#pragma unroll 1
                    for (int k = 0; k < 6; k++) { pace_until(g1, t16); tma2(sb + R_A + k * 9216, &tm_w1, 48 * b, 96 * k, BAR(B_W1)); t16 += time16(9216, W1_GBS, NFFN); }
#pragma unroll 1
                    for (int k = 0; k < 6; k++) { pace_until(g1, t16); tma3(sb + R_C + k * 9216, &tm_w2, 0, 48 * b + 8 * k, 0, BAR(B_W2), pol); t16 += time16(9216, W2_GBS, NFFN); }
                }
                asm volatile("cp.async.bulk.wait_group 0;" ::: "memory");
            }
        }
        if (warp == 10) {
            const int mi = lane >> 3, r8 = lane & 7;
            const uint32_t tag = (epoch + 1u) & 1u, peer = (b & 1) ^ 1;
            const uint32_t one = (lane >> 2) == 0 ? 0x3f803f80u : 0u;
            nbar_sync(NB_P, 160);
            float acc[2][4] = {};
#pragma unroll
            for (int s = 0; s < 4; s++)
#pragma unroll
                for (int mt = 0; mt < 2; mt++) {
                    uint32_t a0, a1, a2, a3;
                    ldsm4(sb + R_P + (16 * mt + (mi & 1) * 8 + r8) * 128 + (((2 * s + (mi >> 1)) ^ r8) << 4), a0, a1, a2, a3);
                    mma16816(acc[mt], a0, a1, a2, a3, one, one);
                }
            if ((lane & 3) == 0) {
                const uint32_t rb = mapa(BAR(B_SL), peer);
#pragma unroll
                for (int k = 0; k < 4; k++) {
                    const uint32_t d = sb + R_ST + 128 + (16 * (k >> 1) + 8 * (k & 1) + (lane >> 2)) * 4;
                    const float l = acc[k >> 1][2 * (k & 1)];
                    stsf(d, l);
                    st_async_f32(mapa(d + 256, peer), l, rb);
                }
            }
            __syncwarp();
            mbar_wait_cluster(BAR(B_ST));
            mbar_wait_cluster(BAR(B_SL));
            const uint32_t a = sb + R_ST + lane * 4;
            const float mo = ldsf(a), lo = ldsf(a + 128), mp = ldsf(a + 256), lp = ldsf(a + 384), m = fmaxf(mo, mp);
            if (((lane >> 2) & 1) == (b & 1))
                sts64(sb + R_STST + (lane >> 3) * 32 + (lane & 3) * 8, tagf(m, tag), tagf(lo * ex2(mo - m) + lp * ex2(mp - m), tag));
            fence_async_smem();
            nbar_arrive(NB_G3, 320);
        }
    }
}

typedef CUresult (*EncodeTiledFn)(CUtensorMap*, CUtensorMapDataType, cuuint32_t, void*, const cuuint64_t*, const cuuint64_t*,
                                  const cuuint32_t*, const cuuint32_t*, CUtensorMapInterleave, CUtensorMapSwizzle,
                                  CUtensorMapL2promotion, CUtensorMapFloatOOBfill);

bool make_map(EncodeTiledFn fn, CUtensorMap* m, const void* base, int rank, const cuuint64_t* dims, const cuuint64_t* strides,
              const cuuint32_t* box, CUtensorMapSwizzle sw) {
    cuuint32_t es[3] = {1, 1, 1};
    return fn(m, CU_TENSOR_MAP_DATA_TYPE_BFLOAT16, rank, const_cast<void*>(base), dims, strides, box, es,
              CU_TENSOR_MAP_INTERLEAVE_NONE, sw, CU_TENSOR_MAP_L2_PROMOTION_NONE, CU_TENSOR_MAP_FLOAT_OOB_FILL_NONE) == CUDA_SUCCESS;
}

}

extern "C" void kernel_launch(void* const* d_in, const int* in_sizes, int n_in, void* d_out, int out_size) {
    (void)in_sizes; (void)n_in; (void)out_size;
    static EncodeTiledFn encode = nullptr;
    if (!encode) {
        void* fn = nullptr;
        cudaDriverEntryPointQueryResult qr;
        cudaGetDriverEntryPoint("cuTensorMapEncodeTiled", &fn, cudaEnableDefault, &qr);
        encode = (EncodeTiledFn)fn;
        cudaFuncSetAttribute(fused_decode_kernel, cudaFuncAttributeMaxDynamicSharedMemorySize, SMEM_BYTES);
    }
    CUtensorMap tm_op, tm_st, tm_wuk, tm_ckv, tm_wuv, tm_wo, tm_w1, tm_w2;
    {
        void* op = nullptr;
        cudaGetSymbolAddress(&op, g_opart);
        cuuint64_t d[4] = {128, 64, 2, 32}, s[3] = {512, 32768, 65536}; cuuint32_t bx[4] = {128, 1, 1, 32}, es[4] = {1, 1, 1, 1};
        encode(&tm_op, CU_TENSOR_MAP_DATA_TYPE_UINT32, 4, op, d, s, bx, es, CU_TENSOR_MAP_INTERLEAVE_NONE, CU_TENSOR_MAP_SWIZZLE_NONE,
               CU_TENSOR_MAP_L2_PROMOTION_NONE, CU_TENSOR_MAP_FLOAT_OOB_FILL_NONE);
        cudaGetSymbolAddress(&op, g_stats);
        cuuint64_t d2[4] = {8, 64, 2, 4}, s2[3] = {32, 2048, 4096}; cuuint32_t bx2[4] = {8, 1, 1, 4};
        encode(&tm_st, CU_TENSOR_MAP_DATA_TYPE_UINT32, 4, op, d2, s2, bx2, es, CU_TENSOR_MAP_INTERLEAVE_NONE, CU_TENSOR_MAP_SWIZZLE_NONE,
               CU_TENSOR_MAP_L2_PROMOTION_NONE, CU_TENSOR_MAP_FLOAT_OOB_FILL_NONE);
    }
    {
        cuuint64_t d[3] = {64, 512, 64}, s[2] = {8192, 128}; cuuint32_t bx[3] = {64, 32, 2};
        make_map(encode, &tm_wuk, d_in[3], 3, d, s, bx, CU_TENSOR_MAP_SWIZZLE_128B);
    }
    {
        cuuint64_t d[3] = {64, 8192, 8}, s[2] = {1024, 128}; cuuint32_t bx[3] = {64, 64, 1};
        make_map(encode, &tm_ckv, d_in[1], 3, d, s, bx, CU_TENSOR_MAP_SWIZZLE_128B);
    }
    {
        cuuint64_t d[3] = {64, 512, 64}, s[2] = {8192, 128}; cuuint32_t bx[3] = {64, 64, 1};
        make_map(encode, &tm_wuv, d_in[4], 3, d, s, bx, CU_TENSOR_MAP_SWIZZLE_128B);
    }
    {
        cuuint64_t d[3] = {64, 4096, 9}, s[2] = {1152, 128}; cuuint32_t bx[3] = {64, 64, 1};
        make_map(encode, &tm_wo, d_in[5], 3, d, s, bx, CU_TENSOR_MAP_SWIZZLE_128B);
    }
    {
        cuuint64_t d[2] = {4608, 576}, s[1] = {9216}; cuuint32_t bx[2] = {48, 96};
        make_map(encode, &tm_w1, d_in[7], 2, d, s, bx, CU_TENSOR_MAP_SWIZZLE_NONE);
    }
    {
        cuuint64_t d[3] = {64, 4608, 9}, s[2] = {1152, 128}; cuuint32_t bx[3] = {64, 8, 9};
        make_map(encode, &tm_w2, d_in[8], 3, d, s, bx, CU_TENSOR_MAP_SWIZZLE_128B);
    }
    Params prm;
    prm.x = (const __nv_bfloat16*)d_in[0];
    prm.wq = (const __nv_bfloat16*)d_in[2];
    prm.w1 = (const char*)d_in[7];
    prm.w2 = (const char*)d_in[8];
    prm.out = (__nv_bfloat16*)d_out;
    fused_decode_kernel<<<NCTA, NTHREADS, SMEM_BYTES, cudaStreamPerThread>>>(tm_op, tm_st, tm_wuk, tm_ckv, tm_wuv, tm_wo, tm_w1, tm_w2, prm);
}
```
